```python
import torch

def _softmax(x, axis=-1):
    return torch.softmax(x, dim=axis)

def _gelu(x):
    return torch.nn.functional.gelu(x, approximate='tanh')

def _silu(x):
    return torch.nn.functional.silu(x)

def _sigmoid(x):
    return torch.sigmoid(x)

def _layernorm(x, axis=-1, eps=1e-05):
    m = x.mean(dim=axis, keepdim=True)
    v = x.var(dim=axis, keepdim=True, unbiased=False)
    return (x - m) / torch.sqrt(v + eps)

def _scatter_add(tgt, idx, src, axis=0):
    return tgt.clone().index_add_(axis, idx, src)

def _segment_sum(src, seg, n):
    out = torch.zeros((n,) + src.shape[1:], dtype=src.dtype)
    return out.index_add_(0, seg, src)

def _pad(x, pw):
    flat = tuple((v for pair in reversed(pw) for v in pair))
    return torch.nn.functional.pad(x, flat)
kernel_name = 'standalone__kv_cache_quant_pre_rope_vs_post_rope__decode'

def setup_inputs():

    _w = lambda a: (lambda t: t.to(torch.bfloat16) if t.is_floating_point() else t)(torch.as_tensor(a))
    B, Sq, Skv = (1, 1, 16384)
    H, Dh0 = (32, 192)
    G = -1 if -1 > 0 else Dh0
    G = max(2, G // 2 * 2)
    Dh = max(G, Dh0 // G * G)
    Skv = max(Skv, Sq)
    ng = Dh // G
    bits = 3 if 3 > 1 else 4
    bits = max(2, min(8, bits))
    qmax = (1 << bits) - 1
    half = Dh // 2
    inv = 1.0 / 10000.0 ** (torch.arange(half) / max(1, half))
    ang_k = torch.arange(Skv)[:, None] * inv[None, :]
    ang_q = torch.arange(Skv - Sq, Skv)[:, None] * inv[None, :]
    kc = torch.cat([torch.cos(ang_k), torch.cos(ang_k)], dim=-1)
    ks = torch.cat([torch.sin(ang_k), torch.sin(ang_k)], dim=-1)
    qc = torch.cat([torch.cos(ang_q), torch.cos(ang_q)], dim=-1)
    qs = torch.cat([torch.sin(ang_q), torch.sin(ang_q)], dim=-1)
    qk_i = torch.randint(0, qmax + 1, (B, H, Skv, Dh)).to(torch.int32)
    qv_i = torch.randint(0, qmax + 1, (B, H, Skv, Dh)).to(torch.int32)
    ksc = torch.abs((lambda *s: torch.randn(*s, dtype=torch.bfloat16) * 0.4)(B, H, Skv, ng)) * 0.1 + 0.01
    kzp = torch.full((B, H, Skv, ng), qmax / 2.0)
    vsc = torch.abs((lambda *s: torch.randn(*s, dtype=torch.bfloat16) * 0.4)(B, H, Skv, ng)) * 0.1 + 0.01
    vzp = torch.full((B, H, Skv, ng), qmax / 2.0)
    return {'q': _w((lambda *s: torch.randn(*s, dtype=torch.bfloat16) * 6.4)(B, H, Sq, Dh) * 0.5), 'qk': _w(qk_i), 'k_scales': _w(ksc), 'k_zeros': _w(kzp), 'qv': _w(qv_i), 'v_scales': _w(vsc), 'v_zeros': _w(vzp), 'q_cos': _w(qc), 'q_sin': _w(qs), 'k_cos': _w(kc), 'k_sin': _w(ks)}

def reference(q, qk, k_scales, k_zeros, qv, v_scales, v_zeros, q_cos, q_sin, k_cos, k_sin):
    B, H, Sq, Dh = q.shape
    ng = k_scales.shape[-1]
    G = Dh // ng
    half = Dh // 2
    ks = (lambda x, n, axis: torch.repeat_interleave(x, n, dim=axis))(k_scales, G, axis=-1)
    kz = (lambda x, n, axis: torch.repeat_interleave(x, n, dim=axis))(k_zeros, G, axis=-1)
    k = ((lambda x, dt: x.to(dt))(qk, q.dtype) - kz) * ks
    vs = (lambda x, n, axis: torch.repeat_interleave(x, n, dim=axis))(v_scales, G, axis=-1)
    vz = (lambda x, n, axis: torch.repeat_interleave(x, n, dim=axis))(v_zeros, G, axis=-1)
    v = ((lambda x, dt: x.to(dt))(qv, q.dtype) - vz) * vs
    k1 = k[..., :half].clone()
    k2 = k[..., half:].clone()
    krh = torch.concatenate([-k2, k1], axis=-1)
    kr = k * k_cos[None, None, :, :] + krh * k_sin[None, None, :, :]
    q1 = q[..., :half].clone()
    q2 = q[..., half:].clone()
    qrh = torch.concatenate([-q2, q1], axis=-1)
    qr = q * q_cos[None, None, :, :] + qrh * q_sin[None, None, :, :]
    logits = torch.einsum('bhqd,bhkd->bhqk', qr, kr) * float(Dh) ** (-0.5)
    attn = _softmax(logits, axis=-1)
    out = torch.einsum('bhqk,bhkd->bhqd', attn, v)
    return out
```

```cpp
#include <cuda_runtime.h>
#include <cuda_bf16.h>
#include <cuda.h>
#include <stdint.h>
#include <stdlib.h>
#include <type_traits>

namespace {

constexpr int H = 32;
constexpr int S = 16384;
constexpr int D = 192;
constexpr int HALF = D / 2;

constexpr int G = 8;
constexpr int T = 4;
constexpr int TEAMS = H / G;
constexpr int UNITS = S / T;
constexpr int STAGES = 3;
#define KV_TAILU 100
#define KV_FROWS 448
#define KV_LAG 20
#define KV_NB 2
constexpr int UA = UNITS - KV_TAILU;
constexpr int TICKETS = UA + 2 * KV_TAILU;
constexpr int F_ROWS = KV_FROWS;
constexpr int P_ROWS = 64;
constexpr int NP = F_ROWS / P_ROWS;
constexpr int F0 = (UA - KV_LAG) * T - F_ROWS;
constexpr int QUARTERS = 4;
constexpr int QC = D / QUARTERS;
constexpr int FINALIZERS = G * QUARTERS;
constexpr int MAX_CPT = 40;
constexpr int GW = 4;
constexpr int SG = 2 * GW;
constexpr int NSL = MAX_CPT / SG;
constexpr int RSLOTS = 16;
constexpr int RSTRIDE = 52;
constexpr int SLOT_WORDS = QUARTERS * 64;

constexpr int W_FIN = 1;
constexpr int W_GATHER = 2;
constexpr int W_CONS = W_GATHER + GW;
constexpr int THREADS = (W_CONS + G) * 32;

constexpr int KV_BYTES = G * T * D * 4;
constexpr int ROWS_BYTES = T * D * 4;
constexpr int CS_BYTES = T * D * 2;
constexpr int SC_BYTES = G * 8 * 2;
constexpr int OFF_K = 0;
constexpr int OFF_V = KV_BYTES;
constexpr int OFF_COS = 2 * KV_BYTES;
constexpr int OFF_SIN = OFF_COS + CS_BYTES;
constexpr int OFF_KS = OFF_SIN + CS_BYTES;
constexpr int OFF_KZ = OFF_KS + SC_BYTES;
constexpr int OFF_VS = OFF_KZ + SC_BYTES;
constexpr int OFF_VZ = OFF_VS + SC_BYTES;
constexpr int STAGE_BYTES = OFF_VZ + SC_BYTES;
constexpr int KSIDE_BYTES = STAGE_BYTES - KV_BYTES;
constexpr int PIECE_BYTES = P_ROWS * QC * 4;

constexpr int BAR_FULLK = 0;
constexpr int BAR_FULLV = 8 * STAGES;
constexpr int BAR_EMPTY = 16 * STAGES;
constexpr int BAR_INIT = 24 * STAGES;
constexpr int BAR_END = BAR_INIT + 8;
constexpr int BAR_W = BAR_END + 8;
constexpr int BAR_G = BAR_W + 8;
constexpr int BAR_FIN = BAR_G + 8 * GW;
constexpr int OFF_UIDX = 224;
constexpr int OFF_TAG = OFF_UIDX + 4 * STAGES;
constexpr int OFF_TICKET = OFF_TAG + 4;
constexpr int LAST_BIT = 1 << 30;
constexpr int TAG_SHIFT = 29;
constexpr int POS_MASK = (1 << TAG_SHIFT) - 1;
constexpr int CTRL_BYTES = 256;
constexpr int OFF_W = CTRL_BYTES + STAGES * STAGE_BYTES;
constexpr int OFF_RV = OFF_W + F_ROWS * 4;
constexpr int OFF_RG = OFF_RV + RSLOTS * RSTRIDE * 4;
constexpr int OFF_GB = OFF_W + KV_BYTES;
constexpr int SMEM_USED = OFF_W + 2 * KV_BYTES;
static_assert(MAX_CPT * RSTRIDE * 4 <= KV_BYTES / 2, "gather buffer");
static_assert(OFF_RG + SG * RSTRIDE * 4 <= OFF_W + KV_BYTES / 2 && NP <= 2 * STAGES + 2, "final-phase buffers");
static_assert(BAR_FIN + 8 * NP <= OFF_UIDX && OFF_TICKET % 8 == 0, "control block");
constexpr int SMEM_BYTES = SMEM_USED;
#define TR_LAND(bytes)
#define TR_STAMP(i)
#define TR_SET(i)
#define TR_EG(i)
static_assert(STAGE_BYTES % 128 == 0 && PIECE_BYTES % 128 == 0, "alignment");
static_assert(SMEM_BYTES <= 232448, "shared memory budget");

struct __align__(128) Scratch {
    float part[H * MAX_CPT * SLOT_WORDS];
    uint2 logit[H * F_ROWS];
    unsigned int mbox[H * QUARTERS * GW * 32];
    unsigned long long ctr[16];
};
__device__ Scratch g_scratch;

__device__ __forceinline__ uint32_t smem_u32(const void* p) {
    return (uint32_t)__cvta_generic_to_shared(p);
}
__device__ __forceinline__ void mbar_init(uint32_t bar, int cnt) {
    asm volatile("mbarrier.init.shared::cta.b64 [%0], %1;" ::"r"(bar), "r"(cnt) : "memory");
}
__device__ __forceinline__ void mbar_expect_tx(uint32_t bar, uint32_t bytes) {
    asm volatile("mbarrier.arrive.expect_tx.shared::cta.b64 _, [%0], %1;" ::"r"(bar), "r"(bytes) : "memory");
}
__device__ __forceinline__ void mbar_arrive(uint32_t bar) {
    asm volatile("mbarrier.arrive.shared::cta.b64 _, [%0];" ::"r"(bar) : "memory");
}
__device__ __forceinline__ void mbar_wait(uint32_t bar, uint32_t parity) {
    asm volatile(
        "{\n"
        ".reg .pred p;\n"
        ".reg .u32 n;\n"
        "mov.u32 n, 0;\n"
        "WAIT_%=:\n"
        "add.u32 n, n, 1;\n"
        "mbarrier.try_wait.parity.shared::cta.b64 p, [%0], %1;\n"
        "setp.gt.or.u32 p, n, 0x40000, p;\n"
        "@!p bra WAIT_%=;\n"
        "}" ::"r"(bar), "r"(parity) : "memory");
}
__device__ __forceinline__ bool mbar_test(uint32_t bar, uint32_t parity) {
    uint32_t ok;
    asm volatile("{\n.reg .pred p;\nmbarrier.test_wait.parity.shared::cta.b64 p, [%1], %2;\nselp.u32 %0, 1, 0, p;\n}"
                 : "=r"(ok) : "r"(bar), "r"(parity) : "memory");
    return ok != 0;
}
__device__ __forceinline__ bool elect_one() {
    uint32_t p;
    asm volatile("{\n.reg .pred p;\nelect.sync _|p, 0xffffffff;\nselp.u32 %0, 1, 0, p;\n}" : "=r"(p));
    return p != 0;
}
__device__ __forceinline__ void bulk_load(uint32_t dst, const void* src, uint32_t bytes, uint32_t bar) {
    asm volatile("cp.async.bulk.shared::cluster.global.mbarrier::complete_tx::bytes [%0], [%1], %2, [%3];"
                 ::"r"(dst), "l"(src), "r"(bytes), "r"(bar) : "memory");
}
__device__ __forceinline__ void bulk_load(uint32_t dst, const void* src, uint32_t bytes, uint32_t bar, uint64_t pol) {
    asm volatile("cp.async.bulk.shared::cluster.global.mbarrier::complete_tx::bytes.L2::cache_hint"
                 " [%0], [%1], %2, [%3], %4;"
                 ::"r"(dst), "l"(src), "r"(bytes), "r"(bar), "l"(pol) : "memory");
}
__device__ __forceinline__ void tma3d(uint32_t dst, const CUtensorMap* map, int c0, int c1, int c2,
                                      uint32_t bar, uint64_t pol) {
    asm volatile(
        "cp.async.bulk.tensor.3d.shared::cluster.global.mbarrier::complete_tx::bytes.L2::cache_hint"
        " [%0], [%1, {%2, %3, %4}], [%5], %6;"
        ::"r"(dst), "l"(map), "r"(c0), "r"(c1), "r"(c2), "r"(bar), "l"(pol) : "memory");
}
__device__ __forceinline__ void tma2d(uint32_t dst, const CUtensorMap* map, int c0, int c1, uint32_t bar) {
    asm volatile(
        "cp.async.bulk.tensor.2d.shared::cluster.global.mbarrier::complete_tx::bytes"
        " [%0], [%1, {%2, %3}], [%4];"
        ::"r"(dst), "l"(map), "r"(c0), "r"(c1), "r"(bar) : "memory");
}
__device__ __forceinline__ void prefetch_map(const CUtensorMap* map) {
    asm volatile("prefetch.tensormap [%0];" ::"l"(map) : "memory");
}
__device__ __forceinline__ uint64_t evict_first_policy() {
    uint64_t pol;
    asm volatile("createpolicy.fractional.L2::evict_first.b64 %0, 1.0;" : "=l"(pol));
    return pol;
}
__device__ __forceinline__ float ex2(float x) {
    float y;
    asm("ex2.approx.ftz.f32 %0, %1;" : "=f"(y) : "f"(x));
    return y;
}
__device__ __forceinline__ float bf_lo(uint32_t x) { return __uint_as_float(x << 16); }
__device__ __forceinline__ float bf_hi(uint32_t x) { return __uint_as_float(x & 0xffff0000u); }
__device__ __forceinline__ uint32_t bf2_mul(uint32_t a, uint32_t b) {
    uint32_t d;
    asm("mul.rn.bf16x2 %0, %1, %2;" : "=r"(d) : "r"(a), "r"(b));
    return d;
}
__device__ __forceinline__ uint32_t bf2_add(uint32_t a, uint32_t b) {
    uint32_t d;
    asm("add.rn.bf16x2 %0, %1, %2;" : "=r"(d) : "r"(a), "r"(b));
    return d;
}
__device__ __forceinline__ uint32_t bf2_sub(uint32_t a, uint32_t b) {
    uint32_t d;
    asm("sub.rn.bf16x2 %0, %1, %2;" : "=r"(d) : "r"(a), "r"(b));
    return d;
}
__device__ __forceinline__ float lds_bf16(uint32_t addr) {
    unsigned short v;
    asm volatile("ld.shared.u16 %0, [%1];" : "=h"(v) : "r"(addr));
    return __uint_as_float(((uint32_t)v) << 16);
}
__device__ __forceinline__ int4 lds128(uint32_t addr) {
    int4 v;
    asm volatile("ld.shared.v4.s32 {%0,%1,%2,%3}, [%4];" : "=r"(v.x), "=r"(v.y), "=r"(v.z), "=r"(v.w) : "r"(addr));
    return v;
}
__device__ __forceinline__ uint2 lds64(uint32_t addr) {
    uint2 v;
    asm volatile("ld.shared.v2.u32 {%0,%1}, [%2];" : "=r"(v.x), "=r"(v.y) : "r"(addr));
    return v;
}
__device__ __forceinline__ float2 lds64f(uint32_t addr) {
    const uint2 v = lds64(addr);
    return make_float2(__uint_as_float(v.x), __uint_as_float(v.y));
}
__device__ __forceinline__ uint32_t lds32(uint32_t addr) {
    uint32_t v;
    asm volatile("ld.shared.u32 %0, [%1];" : "=r"(v) : "r"(addr) : "memory");
    return v;
}
__device__ __forceinline__ void sts32(uint32_t addr, uint32_t v) {
    asm volatile("st.shared.u32 [%0], %1;" ::"r"(addr), "r"(v) : "memory");
}
__device__ __forceinline__ void sts128f(uint32_t addr, float a, float b, float c, float d) {
    asm volatile("st.shared.v4.f32 [%0], {%1,%2,%3,%4};" ::"r"(addr), "f"(a), "f"(b), "f"(c), "f"(d) : "memory");
}
__device__ __forceinline__ float warp_max(float x) {
    int k = __float_as_int(x);
    k ^= (k >> 31) & 0x7fffffff;
    k = __reduce_max_sync(0xffffffffu, k);
    return __int_as_float(k ^ ((k >> 31) & 0x7fffffff));
}

__device__ __forceinline__ uint32_t tagged(float x, uint32_t tag) { return (__float_as_uint(x) & ~1u) | tag; }

__device__ __forceinline__ void st_relaxed_b64(const void* p, uint32_t lo, uint32_t hi) {
    asm volatile("{\n.reg .b64 v;\nmov.b64 v, {%1,%2};\nst.relaxed.gpu.global.b64 [%0], v;\n}"
                 ::"l"(p), "r"(lo), "r"(hi) : "memory");
}
template <int OFF>
__device__ __forceinline__ void ld_relaxed_2xb64_if(uint4& v, const void* base, int pred) {
    asm volatile("{\n.reg .pred p;\n.reg .b64 a, b;\nsetp.ne.s32 p, %5, 0;\n"
                 "mov.b64 a, {%0,%1};\nmov.b64 b, {%2,%3};\n"
                 "@p ld.relaxed.gpu.global.v2.b64 {a, b}, [%4+%6];\n"
                 "mov.b64 {%0,%1}, a;\nmov.b64 {%2,%3}, b;\n}"
                 : "+r"(v.x), "+r"(v.y), "+r"(v.z), "+r"(v.w) : "l"(base), "r"(pred), "n"(OFF) : "memory");
}
__device__ __forceinline__ void mbox_post(unsigned int* box, unsigned int bits) {
    asm volatile("red.relaxed.gpu.global.or.b32 [%0], %1;" ::"l"(box), "r"(bits) : "memory");
}
__device__ __forceinline__ unsigned int mbox_take(unsigned int* box) {
    unsigned int v;
    asm volatile("atom.relaxed.gpu.global.exch.b32 %0, [%1], 0;" : "=r"(v) : "l"(box) : "memory");
    return v;
}
template <int OFF>
__device__ __forceinline__ uint2 ldg64(const void* base) {
    uint2 v;
    asm volatile("ld.global.nc.v2.u32 {%0,%1}, [%2+%3];" : "=r"(v.x), "=r"(v.y) : "l"(base), "n"(OFF));
    return v;
}
template <int N, typename F>
__device__ __forceinline__ void static_for(F&& f) {
    if constexpr (N > 0) {
        static_for<N - 1>(f);
        f(std::integral_constant<int, N - 1>{});
    }
}
__device__ __forceinline__ unsigned long long draw(unsigned long long* ctr, unsigned long long inc) {
    unsigned long long v;
    asm volatile("atom.relaxed.gpu.global.add.u64 %0, [%1], %2;" : "=l"(v) : "l"(ctr), "l"(inc) : "memory");
    return v;
}

__device__ __forceinline__ uint32_t piece_off(int p) {
    return CTRL_BYTES + KV_BYTES / 2 + (p >> 1) * STAGE_BYTES + (p & 1) * KV_BYTES;
}
static_assert(PIECE_BYTES == KV_BYTES / 2 && OFF_K == 0 && OFF_V == KV_BYTES, "piece placement");

struct Params {
    const int* qk;
    const int* qv;
    const __nv_bfloat16* k_cos;
    const __nv_bfloat16* k_sin;
    Scratch* scratch;
    const __nv_bfloat16* q;
    const __nv_bfloat16* q_cos;
    const __nv_bfloat16* q_sin;
    __nv_bfloat16* out;
    int tw, fe, rank1, open, openw, ctl0, thr, dith, ooo, delay, mstr;
};
struct Maps {
    CUtensorMap k, v, ks, kz, vs, vz, kh, vh, vf;
};

__global__ void __launch_bounds__(THREADS, 1)
kv_decode_kernel(const __grid_constant__ Params prm, const __grid_constant__ Maps maps) {
    extern __shared__ __align__(1024) unsigned char smem[];
    const int team = blockIdx.x % TEAMS;
    const int cin = blockIdx.x / TEAMS;
    const int h0 = team * G;
    const uint32_t sb = __shfl_sync(0xffffffffu, smem_u32(smem), 0);
    const uint32_t buf0 = sb + CTRL_BYTES;

    if (threadIdx.x < 32 && elect_one()) {
        mbar_init(sb + BAR_FULLK, 1);
        mbar_init(sb + BAR_FULLV, 1);
        asm volatile("fence.mbarrier_init.release.cluster;" ::: "memory");
        const uint64_t pol = evict_first_policy();
        const size_t off = (uint32_t)(h0 * S + cin * T) * (size_t)(D * 4);
#pragma unroll
        for (int i = 0; i < KV_NB; i++) {
            const char* src = reinterpret_cast<const char*>(i ? prm.qv : prm.qk) + off;
#pragma unroll
            for (int g = 0; g < G; g++)
                bulk_load(buf0 + i * KV_BYTES + g * ROWS_BYTES, src + (size_t)g * S * D * 4, ROWS_BYTES,
                          sb + i * BAR_FULLV, pol);
        }
#pragma unroll
        for (int i = 1; i < BAR_FIN / 8 + NP; i++)
            if (i != BAR_FULLV / 8) mbar_init(sb + 8 * i, (unsigned)(i - BAR_EMPTY / 8) < STAGES ? G : 1);
        asm volatile("fence.mbarrier_init.release.cluster;" ::: "memory");
    }

    const int warp = __shfl_sync(0xffffffffu, threadIdx.x >> 5, 0);
    const int lane = threadIdx.x & 31;
    const int cpt = gridDim.x / TEAMS;

    if (warp >= W_CONS) {
        const int cw = warp - W_CONS;
        const int h = h0 + cw;
        const int r = lane >> 3;
        const int j = lane & 7;

        float qa[3][4], qb[3][4];
        {
            const __nv_bfloat16* qp = prm.q + h * D + 4 * j;
            const __nv_bfloat16* cp = prm.q_cos + 4 * j;
            const __nv_bfloat16* sp = prm.q_sin + 4 * j;
            static_for<3>([&](auto ic) {
                constexpr int i = decltype(ic)::value;
                const uint2 x1 = ldg64<64 * i>(qp), x2 = ldg64<64 * i + 2 * HALF>(qp);
                const uint2 c1 = ldg64<64 * i>(cp), c2 = ldg64<64 * i + 2 * HALF>(cp);
                const uint2 s1 = ldg64<64 * i>(sp), s2 = ldg64<64 * i + 2 * HALF>(sp);
                const uint32_t a0 = bf2_sub(bf2_mul(x1.x, c1.x), bf2_mul(x2.x, s1.x));
                const uint32_t a1 = bf2_sub(bf2_mul(x1.y, c1.y), bf2_mul(x2.y, s1.y));
                const uint32_t b0 = bf2_add(bf2_mul(x2.x, c2.x), bf2_mul(x1.x, s2.x));
                const uint32_t b1 = bf2_add(bf2_mul(x2.y, c2.y), bf2_mul(x1.y, s2.y));
                qa[i][0] = bf_lo(a0); qa[i][1] = bf_hi(a0); qa[i][2] = bf_lo(a1); qa[i][3] = bf_hi(a1);
                qb[i][0] = bf_lo(b0); qb[i][1] = bf_hi(b0); qb[i][2] = bf_lo(b1); qb[i][3] = bf_hi(b1);
            });
        }
        float acc[6][4];
#pragma unroll
        for (int i = 0; i < 6; i++)
#pragma unroll
            for (int c = 0; c < 4; c++) acc[i][c] = 0.f;
        float m_run = -INFINITY, l_run = 0.f, z_run = 0.f;

        const uint32_t va_off = OFF_V + ((lane & 16) ? 384 : 0);
        const uint32_t vb_off = OFF_V + ((lane & 16) ? 0 : 384);
        uint32_t kv_off = (uint32_t)((cw * T + r) * (D * 4) + j * 16);
        uint32_t cs_off = (uint32_t)(OFF_COS + r * (D * 2) + j * 8);
        uint32_t sc_off = (uint32_t)(OFF_KS + cw * 16 + r * 2);
        float mask = 0.f;

        asm volatile("bar.sync 0, %0;" ::"n"(THREADS) : "memory");
        TR_STAMP(12);

        int s = 0, word;
        uint32_t ph = 0;
#pragma unroll 1
        do {
            mbar_wait(sb + BAR_FULLK + 8 * s, ph);
            word = (int)lds32(sb + OFF_UIDX + 4 * s);
            const int pos = word & POS_MASK;
            if (pos >= UA * T) {
                kv_off = (uint32_t)((cw * (T / 2) + (r & 1)) * (D * 4) + j * 16);
                cs_off = (uint32_t)(OFF_COS + (r & 1) * (D * 2) + j * 8);
                sc_off = (uint32_t)(OFF_KS + cw * 16 + (r & 1) * 2);
                mask = r >= 2 ? -INFINITY : 0.f;
            }
            TR_LAND((KV_BYTES + 768 + 256) / (pos >= UA * T ? 2 : 1));
            if (cw == 0) TR_EG(2);
            const uint32_t st = buf0 + s * STAGE_BYTES;
            const uint32_t sc = st + sc_off + (pos & 7) * 2;
            const float kz = lds_bf16(sc + SC_BYTES);
            const float ks = lds_bf16(sc) * (0.07216878364870322f * 1.4426950408889634f);
            const float vs = lds_bf16(sc + 2 * SC_BYTES);
            const float vz = lds_bf16(sc + 3 * SC_BYTES);

            float d0 = 0.f, d1 = 0.f;
#pragma unroll
            for (int i = 0; i < 3; i++) {
                const int4 ka = lds128(st + kv_off + i * 128);
                const int4 kb = lds128(st + kv_off + (i + 3) * 128);
                const uint2 ca = lds64(st + cs_off + i * 64);
                const uint2 cb = lds64(st + cs_off + (i + 3) * 64);
                const uint2 sa = lds64(st + cs_off + CS_BYTES + i * 64);
                const uint2 sb2 = lds64(st + cs_off + CS_BYTES + (i + 3) * 64);
                const float a[4] = {(float)ka.x - kz, (float)ka.y - kz, (float)ka.z - kz, (float)ka.w - kz};
                const float b[4] = {(float)kb.x - kz, (float)kb.y - kz, (float)kb.z - kz, (float)kb.w - kz};
                const float fca[4] = {bf_lo(ca.x), bf_hi(ca.x), bf_lo(ca.y), bf_hi(ca.y)};
                const float fcb[4] = {bf_lo(cb.x), bf_hi(cb.x), bf_lo(cb.y), bf_hi(cb.y)};
                const float fsa[4] = {bf_lo(sa.x), bf_hi(sa.x), bf_lo(sa.y), bf_hi(sa.y)};
                const float fsb[4] = {bf_lo(sb2.x), bf_hi(sb2.x), bf_lo(sb2.y), bf_hi(sb2.y)};
#pragma unroll
                for (int c = 0; c < 4; c++) {
                    const float ra = fmaf(a[c], fca[c], -b[c] * fsa[c]);
                    const float rb = fmaf(b[c], fcb[c], a[c] * fsb[c]);
                    d0 = fmaf(qa[i][c], ra, d0);
                    d1 = fmaf(qb[i][c], rb, d1);
                }
            }
            float dot = d0 + d1;
            dot += __shfl_xor_sync(0xffffffffu, dot, 1);
            dot += __shfl_xor_sync(0xffffffffu, dot, 2);
            dot += __shfl_xor_sync(0xffffffffu, dot, 4);
            const float sv = dot * ks;

            if ((unsigned)(pos - F0) < (unsigned)F_ROWS) {
                if (j == 0)
                    st_relaxed_b64(prm.scratch->logit + h * F_ROWS + (pos - F0) + r,
                                   (__float_as_uint(vs) >> 16) | __float_as_uint(vz), tagged(sv, (word >> TAG_SHIFT) & 1));
            } else {
                if (__any_sync(0xffffffffu, sv > m_run)) {
                    float m_new = fmaxf(sv, __shfl_xor_sync(0xffffffffu, sv, 8));
                    m_new = fmaxf(m_run, fmaxf(m_new, __shfl_xor_sync(0xffffffffu, m_new, 16)));
                    const float alpha = ex2(m_run - m_new);
                    l_run *= alpha;
                    z_run *= alpha;
#pragma unroll
                    for (int i = 0; i < 6; i++)
#pragma unroll
                        for (int c = 0; c < 4; c++) acc[i][c] *= alpha;
                    m_run = m_new;
                }
                const float p = ex2(sv - m_run + mask);
                const float pv = p * vs;
                l_run += p;
                z_run = fmaf(pv, vz, z_run);
                mbar_wait(sb + BAR_FULLV + 8 * s, ph);
                TR_LAND(KV_BYTES / (pos >= UA * T ? 2 : 1));
                if (cw == 0) TR_EG(3);
#pragma unroll
                for (int i = 0; i < 6; i++) {
                    const int4 v = lds128(st + kv_off + (i < 3 ? va_off : vb_off) + (i % 3) * 128);
                    acc[i][0] = fmaf(pv, (float)v.x, acc[i][0]);
                    acc[i][1] = fmaf(pv, (float)v.y, acc[i][1]);
                    acc[i][2] = fmaf(pv, (float)v.z, acc[i][2]);
                    acc[i][3] = fmaf(pv, (float)v.w, acc[i][3]);
                }
            }
            __syncwarp();
            if (lane == 0) mbar_arrive(sb + BAR_EMPTY + 8 * s);
            if (++s == STAGES) { s = 0; ph ^= 1; }
        } while (!(word & LAST_BIT));

        {
            const uint32_t tag = (word >> TAG_SHIFT) & 1;
            char* slot = reinterpret_cast<char*>(prm.scratch->part + (h * MAX_CPT + cin) * SLOT_WORDS);
            char* part_st = slot + (lane & 16) * 32 + j * 16 + (lane & 8);
            l_run += __shfl_xor_sync(0xffffffffu, l_run, 8);
            z_run += __shfl_xor_sync(0xffffffffu, z_run, 8);
            l_run += __shfl_xor_sync(0xffffffffu, l_run, 16);
            z_run += __shfl_xor_sync(0xffffffffu, z_run, 16);
            st_relaxed_b64(slot + r * 256 + QC * 4 + j * 8, __float_as_uint(m_run), tagged(l_run, tag));
            const bool od = (lane & 8) != 0;
#pragma unroll
            for (int i = 0; i < 3; i++) {
                float k[4];
#pragma unroll
                for (int c = 0; c < 4; c++) k[c] = acc[i][c] + __shfl_xor_sync(0xffffffffu, acc[i + 3][c], 16);
                const float z0 = (od ? k[2] : k[0]) + __shfl_xor_sync(0xffffffffu, od ? k[0] : k[2], 8);
                const float z1 = (od ? k[3] : k[1]) + __shfl_xor_sync(0xffffffffu, od ? k[1] : k[3], 8);
                st_relaxed_b64(part_st + i * 128 + (i == 2 ? 64 : i == 1 ? (j & 4) * 16 : 0),
                               __float_as_uint(z0 - z_run), tagged(z1 - z_run, tag));
            }
            if (prm.delay) { const unsigned c0 = clock(); while ((unsigned)clock() - c0 < (unsigned)prm.delay) {} }
            if (lane < QUARTERS) mbox_post(prm.scratch->mbox + ((h * QUARTERS + lane) * GW + cin % GW) * prm.mstr, 1u << (cin / GW));
        }
        TR_STAMP(3);

        if (cin >= FINALIZERS || cw >= RSLOTS * 12 / 32) return;
        const int ft = threadIdx.x - W_CONS * 32;
        const int rs = ft / 12;
        float a0 = 0.f, a1 = 0.f, a2 = 0.f, a3 = 0.f;
        mbar_wait(sb + BAR_W, 0);
        const uint32_t ra = sb + OFF_RV + rs * (RSTRIDE * 4 - QC * 4) + ft * 16;
        auto load = [&](int4 (&v)[4], uint32_t addr) {
#pragma unroll
            for (int i = 0; i < 4; i++) v[i] = lds128(addr + i * (RSLOTS * QC * 4));
        };
        auto accumulate = [&](const int4 (&v)[4], const int4& w4) {
            const float w[4] = {__int_as_float(w4.x), __int_as_float(w4.y), __int_as_float(w4.z), __int_as_float(w4.w)};
#pragma unroll
            for (int i = 0; i < 4; i++) {
                a0 = fmaf(w[i], (float)v[i].x, a0);
                a1 = fmaf(w[i], (float)v[i].y, a1);
                a2 = fmaf(w[i], (float)v[i].z, a2);
                a3 = fmaf(w[i], (float)v[i].w, a3);
            }
        };
        int4 v[4], w = lds128(sb + OFF_W + rs * 16);
        mbar_wait(sb + BAR_FIN, 0);
        load(v, sb + piece_off(0) + ft * 16);
#pragma unroll 1
        for (int p = 1; p < NP; p++) {
            const int4 wn = lds128(sb + OFF_W + p * (P_ROWS * 4) + rs * 16);
            const uint32_t va = sb + piece_off(p) + ft * 16;
            if (mbar_test(sb + BAR_FIN + 8 * p, 0)) {
                int4 vn[4];
                load(vn, va);
                accumulate(v, w);
#pragma unroll
                for (int i = 0; i < 4; i++) v[i] = vn[i];
            } else {
                accumulate(v, w);
                mbar_wait(sb + BAR_FIN + 8 * p, 0);
                load(v, va);
            }
            w = wn;
        }
        accumulate(v, w);
        sts128f(ra, a0, a1, a2, a3);
        asm volatile("bar.arrive 3, %0;" ::"n"(RSLOTS * 12 + 32) : "memory");
        return;
    }

    if (warp >= W_GATHER) {
        if (warp == W_GATHER && lane < 2 * G) {
            const size_t off = (uint32_t)((h0 + (lane & 7)) * S + cin * T) * (size_t)(D * 4);
            asm volatile("prefetch.global.L2 [%0];" ::"l"(reinterpret_cast<const char*>(lane < G ? prm.qk : prm.qv) + off));
        }
        asm volatile("bar.sync 0, %0;" ::"n"(THREADS) : "memory");
        if (cin >= FINALIZERS) return;
        const int gw = warp - W_GATHER;
        const int n = (cpt - gw + GW - 1) / GW;
        const float* src = prm.scratch->part + ((h0 + cin / QUARTERS) * MAX_CPT + gw) * SLOT_WORDS + (cin % QUARTERS) * 64;
        const uint32_t dst = sb + OFF_GB + gw * (RSTRIDE * 4);
        const uint32_t bar = sb + BAR_G + 8 * gw;
        unsigned int* box = prm.scratch->mbox + ((h0 * QUARTERS + cin) * GW + gw) * prm.mstr;
        mbar_wait(sb + BAR_END, 0);
        const uint32_t tag = lds32(sb + OFF_TAG);
        const int sub = lane >= 13, quad = min(lane - sub * 13, 12);
        const int sg = 2 * gw + sub;
        uint4 dt[NSL];
        for (int attempt = 0; attempt < (1 << 12); attempt++) {
            if (elect_one()) {
                mbar_expect_tx(bar, n * (RSTRIDE * 4));
                unsigned want = (1u << n) - 1;
                int spin = 0;
                do {
                    unsigned got = attempt ? want : mbox_take(box);
                    want &= ~got;
                    while (got) {
                        const int i = __ffs(got) - 1;
                        got &= got - 1;
                        bulk_load(dst + i * (GW * RSTRIDE * 4), src + i * (GW * SLOT_WORDS), RSTRIDE * 4, bar);
                    }
                } while (want && ++spin < (1 << 20));
            }
            mbar_wait(bar, attempt & 1);
            uint32_t bad = 0;
#pragma unroll
            for (int b = 0; b < NSL; b++) {
                dt[b] = make_uint4(quad == 12 ? 0xff800000u : 0u, tag, 0u, tag);
                if (2 * b + sub < n) {
                    const int4 v = lds128(dst + (2 * b + sub) * (GW * RSTRIDE * 4) + quad * 16);
                    dt[b] = make_uint4(v.x, v.y, v.z, v.w);
                }
                bad |= (dt[b].y ^ tag) | (dt[b].w ^ tag);
            }
            if (!__any_sync(0xffffffffu, bad & 1u)) break;
            asm volatile("fence.proxy.async.shared::cta;" ::: "memory");
        }
        TR_STAMP(4);
        float mh[NSL], m = -INFINITY;
#pragma unroll
        for (int b = 0; b < NSL; b++) {
            mh[b] = __shfl_sync(0xffffffffu, __uint_as_float(dt[b].x), sub * 13 + 12);
            m = fmaxf(m, mh[b]);
        }
        float a0 = 0.f, a1 = 0.f, a2 = 0.f, a3 = 0.f;
#pragma unroll
        for (int b = 0; b < NSL; b++) {
            const float w = ex2(mh[b] - m);
            a0 = fmaf(w, __uint_as_float(dt[b].x), a0);
            a1 = fmaf(w, __uint_as_float(dt[b].y), a1);
            a2 = fmaf(w, __uint_as_float(dt[b].z), a2);
            a3 = fmaf(w, __uint_as_float(dt[b].w), a3);
        }
        if (lane < 26) sts128f(sb + OFF_RG + sg * (RSTRIDE * 4) + quad * 16, quad == 12 ? m : a0, a1, a2, a3);
        asm volatile("bar.arrive 2, %0;" ::"n"(GW * 32 + 32) : "memory");
        return;
    }

    if (warp == W_FIN) {
        if (elect_one()) {
            prefetch_map(&maps.ks);
            prefetch_map(&maps.kz);
            prefetch_map(&maps.vs);
            prefetch_map(&maps.vz);
            prefetch_map(&maps.k);
            prefetch_map(&maps.v);
        }
        asm volatile("bar.sync 0, %0;" ::"n"(THREADS) : "memory");
        if (cin >= FINALIZERS) return;
        const char* lptr = reinterpret_cast<const char*>(prm.scratch->logit + (h0 + cin / QUARTERS) * F_ROWS) + lane * 16;
        __nv_bfloat16* optr = prm.out + h0 * D + cin * QC + 2 * lane;
        mbar_wait(sb + BAR_INIT, 0);
        const uint32_t tag = lds32(sb + OFF_TAG);
        uint4 rec[NP];
        bool ok;
        int spin = 0;
        do {
            static_for<NP>([&](auto ic) { ld_relaxed_2xb64_if<decltype(ic)::value * 512>(rec[decltype(ic)::value], lptr, 1); });
            uint32_t bad = 0;
#pragma unroll
            for (int i = 0; i < NP; i++) bad |= (rec[i].y ^ tag) | (rec[i].w ^ tag);
            ok = (bad & 1u) == 0;
        } while (!__all_sync(0xffffffffu, ok) && ++spin < (1 << 20));
        float mF = -INFINITY, lF = 0.f, zF = 0.f;
#pragma unroll
        for (int i = 0; i < NP; i++) mF = fmaxf(mF, fmaxf(__uint_as_float(rec[i].y), __uint_as_float(rec[i].w)));
        mF = warp_max(mF);
        const uint32_t wa = sb + OFF_W + (lane & 7) * 32 + (lane >> 3) * 4;
#pragma unroll
        for (int i = 0; i < NP; i++) {
            const float p0 = ex2(__uint_as_float(rec[i].y) - mF), p1 = ex2(__uint_as_float(rec[i].w) - mF);
            const float a0 = p0 * bf_lo(rec[i].x), a1 = p1 * bf_lo(rec[i].z);
            lF += p0 + p1;
            zF = fmaf(a0, bf_hi(rec[i].x), fmaf(a1, bf_hi(rec[i].z), zF));
            sts32(wa + i * (P_ROWS * 4), __float_as_uint(a0));
            sts32(wa + i * (P_ROWS * 4) + 16, __float_as_uint(a1));
        }
        __syncwarp();
        if (lane == 0) mbar_arrive(sb + BAR_W);
#pragma unroll
        for (int o = 16; o > 0; o >>= 1) {
            lF += __shfl_xor_sync(0xffffffffu, lF, o);
            zF += __shfl_xor_sync(0xffffffffu, zF, o);
        }
        const uint32_t col = sb + (uint32_t)min(lane, QC / 2 - 1) * 8;
        asm volatile("bar.sync 2, %0;" ::"r"(__float_as_uint(lF + zF) == 0xffffffffu ? 32 : GW * 32 + 32) : "memory");
        TR_EG(6);
        float2 ml[SG], ga[SG];
#pragma unroll
        for (int g = 0; g < SG; g++) {
            ml[g] = lds64f(sb + OFF_RG + g * (RSTRIDE * 4) + QC * 4);
            ga[g] = lds64f(col + OFF_RG + g * (RSTRIDE * 4));
        }
        float M = mF;
#pragma unroll
        for (int g = 0; g < SG; g++) M = fmaxf(M, ml[g].x);
        float wF = ex2(mF - M);
        float L = wF * lF, b0 = -wF * zF, b1 = b0;
#pragma unroll
        for (int g = 0; g < SG; g++) {
            const float w = ex2(ml[g].x - M);
            L = fmaf(w, ml[g].y, L);
            b0 = fmaf(w, ga[g].x, b0);
            b1 = fmaf(w, ga[g].y, b1);
        }
        const float inv = __fdividef(1.f, L);
        wF *= inv;
        b0 *= inv;
        b1 *= inv;
        TR_STAMP(5);
        asm volatile("bar.sync 3, %0;"
                     ::"r"(__any_sync(0xffffffffu, __float_as_uint(wF + b0 + b1) == 0xffffffffu) ? 32 : RSLOTS * 12 + 32) : "memory");
        float2 rv[RSLOTS];
#pragma unroll
        for (int g = 0; g < RSLOTS; g++) rv[g] = lds64f(col + OFF_RV + g * (RSTRIDE * 4));
        static_for<4>([&](auto lc) {
            constexpr int o = RSLOTS / 2 >> decltype(lc)::value;
#pragma unroll
            for (int g = 0; g < o; g++) {
                rv[g].x += rv[g + o].x;
                rv[g].y += rv[g + o].y;
            }
        });
        if (lane < QC / 2)
            *reinterpret_cast<__nv_bfloat162*>(optr) = __floats2bfloat162_rn(fmaf(wF, rv[0].x, b0), fmaf(wF, rv[0].y, b1));
        TR_STAMP(6);
        return;
    }

    __syncwarp();
    asm volatile("bar.arrive 0, %0;" ::"n"(THREADS) : "memory");
    if (!elect_one()) return;
    const uint64_t pol = evict_first_policy();
    unsigned long long* ctr = prm.scratch->ctr;
    const int total = TICKETS - (STAGES - 1) * cpt;
    const unsigned long long inc = 1ull << (15 * team);
    unsigned long long ticket = draw(ctr, inc);
    uint32_t w1 = (sb + BAR_END) | 1, w2 = w1, w3 = w1, w4 = w1, w5 = w1;
    auto gate = [&](int win) {
        const uint32_t w = win == 2 ? w2 : win == 3 ? w3 : win == 4 ? w4 : w5;
        if (win <= 5) mbar_wait(w & ~1u, w & 1u);
    };
    auto push = [&](uint32_t w) { w5 = w4; w4 = w3; w3 = w2; w2 = w1; w1 = w; };
    int s = 0, u = cin, k = 0, halves = 0, ahead = 0, drawn = 0;
    uint32_t ph = 0;
    bool init_done = false;
#pragma unroll 1
    for (;; k++) {
        const bool half = u >= UA;
        const int pos = half ? (u + UA) * (T / 2) : u * T;
        const int p8 = pos & ~7;
        const uint32_t fb = sb + BAR_FULLK + 8 * s;
        const uint32_t fv = sb + BAR_FULLV + 8 * s;
        const uint32_t dst = buf0 + s * STAGE_BYTES;
        halves += half;
        const int win = (halves < 3 ? 3 : prm.tw) - ahead;
        mbar_wait(sb + BAR_EMPTY + 8 * s, ph ^ 1);
        if (k >= STAGES) gate(win);
        if (k > 0) tma3d(dst + OFF_K, half ? &maps.kh : &maps.k, 0, pos, h0, fb, pol);
        bulk_load(dst + OFF_COS, prm.k_cos + (size_t)pos * D, half ? CS_BYTES / 2 : CS_BYTES, fb);
        bulk_load(dst + OFF_SIN, prm.k_sin + (size_t)pos * D, half ? CS_BYTES / 2 : CS_BYTES, fb);
        tma2d(dst + OFF_KS, &maps.ks, p8, h0, fb);
        tma2d(dst + OFF_KZ, &maps.kz, p8, h0, fb);
        tma2d(dst + OFF_VS, &maps.vs, p8, h0, fb);
        tma2d(dst + OFF_VZ, &maps.vz, p8, h0, fb);
        if (k >= STAGES) ticket = draw(ctr, inc);
        TR_EG(0);
        push(fb | ph);
        if ((unsigned)(pos - F0) < (unsigned)F_ROWS) {
            mbar_arrive(fv);
            prefetch_map(&maps.kh);
            prefetch_map(&maps.vh);
            prefetch_map(&maps.vf);
        } else {
            if (k >= STAGES) gate(win);
            mbar_expect_tx(fv, half ? KV_BYTES / 2 : KV_BYTES);
            if (2 * k + 1 >= KV_NB) tma3d(dst + OFF_V, half ? &maps.vh : &maps.v, 0, pos, h0, fv, pol);
            TR_EG(1);
            push(fv | ph);
        }
        int un = u + cpt;
        uint32_t tag = 0;
        if (k >= STAGES - 1) {
            uint32_t lo, hi;
            asm volatile("st.shared.b64 [%2], %3;\nld.volatile.shared.v2.u32 {%0,%1}, [%2];"
                         : "=r"(lo), "=r"(hi) : "r"(sb + OFF_TICKET), "l"(ticket) : "memory");
            const int t01 = (int)(lo & 0x3fffffff), t23 = (int)(__funnelshift_r(lo, hi, 30) & 0x3fffffff);
            const int t = ((team & 2 ? t23 : t01) >> (15 * (team & 1))) & 0x7fff;
            drawn = (t01 & 0x7fff) + (t01 >> 15) + (t23 & 0x7fff) + (t23 >> 15);
            tag = ~hi >> 31;
            un = STAGES * cpt + t;
            ahead = un >= prm.ctl0 && 4 * t - drawn > prm.thr + (int)((un * 5) & prm.dith);
        }
        const bool start_fin = !init_done && un >= TICKETS - 2 * cpt;
        init_done |= start_fin;
        sts32(sb + OFF_UIDX + 4 * s, pos | (tag << TAG_SHIFT) | (un >= TICKETS ? LAST_BIT : 0));
        mbar_expect_tx(fb, half ? KSIDE_BYTES - KV_BYTES / 2 - CS_BYTES : KSIDE_BYTES);
        if (start_fin) {
            sts32(sb + OFF_TAG, tag);
            mbar_arrive(sb + BAR_INIT);
        }
        if (un >= TICKETS) break;
        u = un;
        if (++s == STAGES) { s = 0; ph ^= 1; }
    }
    mbar_arrive(sb + BAR_END);
    if (drawn == TEAMS * total - 1) draw(ctr, (1ull << 63) - total * 0x0000200040008001ull);
    if (cin >= FINALIZERS) return;
    if (halves < STAGES) mbar_wait(sb + BAR_EMPTY + 8 * s, ph);
    const int finw = prm.fe + (TEAMS * total - drawn <= prm.rank1);
#pragma unroll 1
    for (int p = 0; p < NP; p++) {
        const uint32_t fb = sb + BAR_FIN + 8 * p;
        if (halves >= STAGES || p >= 5) gate(p >= NP - prm.open ? finw + prm.openw : finw);
        mbar_expect_tx(fb, PIECE_BYTES);
        tma3d(sb + piece_off(p), &maps.vf, (cin % QUARTERS) * QC, F0 + p * P_ROWS, h0 + cin / QUARTERS, fb, pol);
        TR_EG(8 + p);
        push(fb);
    }
}

typedef CUresult (*EncodeTiledFn)(CUtensorMap*, CUtensorMapDataType, cuuint32_t, void*, const cuuint64_t*,
                                  const cuuint64_t*, const cuuint32_t*, const cuuint32_t*,
                                  CUtensorMapInterleave, CUtensorMapSwizzle, CUtensorMapL2promotion,
                                  CUtensorMapFloatOOBfill);

void make_kv_map(EncodeTiledFn enc, CUtensorMap* m, const void* ptr, int cols, int rows, int heads,
                 CUtensorMapL2promotion promo) {
    cuuint64_t dims[3] = {(cuuint64_t)D, (cuuint64_t)S, (cuuint64_t)H};
    cuuint64_t strides[2] = {(cuuint64_t)D * 4, (cuuint64_t)S * D * 4};
    cuuint32_t box[3] = {(cuuint32_t)cols, (cuuint32_t)rows, (cuuint32_t)heads};
    cuuint32_t es[3] = {1, 1, 1};
    enc(m, CU_TENSOR_MAP_DATA_TYPE_INT32, 3, const_cast<void*>(ptr), dims, strides, box, es,
        CU_TENSOR_MAP_INTERLEAVE_NONE, CU_TENSOR_MAP_SWIZZLE_NONE, promo, CU_TENSOR_MAP_FLOAT_OOB_FILL_NONE);
}

void make_scale_map(EncodeTiledFn enc, CUtensorMap* m, const void* ptr) {
    cuuint64_t dims[2] = {(cuuint64_t)S, (cuuint64_t)H};
    cuuint64_t strides[1] = {(cuuint64_t)S * 2};
    cuuint32_t box[2] = {8, (cuuint32_t)G};
    cuuint32_t es[2] = {1, 1};
    enc(m, CU_TENSOR_MAP_DATA_TYPE_BFLOAT16, 2, const_cast<void*>(ptr), dims, strides, box, es,
        CU_TENSOR_MAP_INTERLEAVE_NONE, CU_TENSOR_MAP_SWIZZLE_NONE, CU_TENSOR_MAP_L2_PROMOTION_NONE,
        CU_TENSOR_MAP_FLOAT_OOB_FILL_NONE);
}

}

extern "C" void kernel_launch(void* const* d_in, const int* in_sizes, int n_in, void* d_out, int out_size) {
    (void)in_sizes; (void)n_in; (void)out_size;
    static EncodeTiledFn enc = nullptr;
    static Scratch* scratch = nullptr;
    static int grid = 0;
    if (!enc) {
        void* fn = nullptr;
        cudaDriverEntryPointQueryResult qr;
        cudaGetDriverEntryPoint("cuTensorMapEncodeTiled", &fn, cudaEnableDefault, &qr);
        enc = (EncodeTiledFn)fn;
        int dev = 0, sms = 0;
        cudaGetDevice(&dev);
        cudaDeviceGetAttribute(&sms, cudaDevAttrMultiProcessorCount, dev);
        int cpt = sms / TEAMS;
        if (cpt > MAX_CPT) cpt = MAX_CPT;
        grid = cpt * TEAMS;
        cudaGetSymbolAddress((void**)&scratch, g_scratch);
        cudaFuncSetAttribute(kv_decode_kernel, cudaFuncAttributeMaxDynamicSharedMemorySize, SMEM_BYTES);
    }
    Params prm;
    prm.q = (const __nv_bfloat16*)d_in[0];
    prm.qk = (const int*)d_in[1];
    prm.qv = (const int*)d_in[4];
    prm.q_cos = (const __nv_bfloat16*)d_in[7];
    prm.q_sin = (const __nv_bfloat16*)d_in[8];
    prm.k_cos = (const __nv_bfloat16*)d_in[9];
    prm.k_sin = (const __nv_bfloat16*)d_in[10];
    prm.out = (__nv_bfloat16*)d_out;
    prm.scratch = scratch;
    auto env = [](const char* n, int d) { const char* e = getenv(n); return e ? atoi(e) : d; };
    prm.tw = env("TW", 4); prm.fe = env("FE", 3); prm.rank1 = env("RANK1", 0);
    prm.open = env("OPEN", 1); prm.openw = env("OPENW", 1);
    prm.ctl0 = env("CTL0", 100000); prm.thr = env("THR", 8); prm.dith = env("DITH", 0);
    prm.ooo = env("OOO", 1); prm.delay = env("DELAY", 0); prm.mstr = env("MSTR", 32);
    Maps maps;
    make_kv_map(enc, &maps.k, prm.qk, D, T, G, CU_TENSOR_MAP_L2_PROMOTION_L2_128B);
    make_kv_map(enc, &maps.v, prm.qv, D, T, G, CU_TENSOR_MAP_L2_PROMOTION_L2_128B);
    make_kv_map(enc, &maps.kh, prm.qk, D, T / 2, G, CU_TENSOR_MAP_L2_PROMOTION_L2_128B);
    make_kv_map(enc, &maps.vh, prm.qv, D, T / 2, G, CU_TENSOR_MAP_L2_PROMOTION_L2_128B);
    make_kv_map(enc, &maps.vf, prm.qv, QC, P_ROWS, 1, CU_TENSOR_MAP_L2_PROMOTION_NONE);
    make_scale_map(enc, &maps.ks, d_in[2]);
    make_scale_map(enc, &maps.kz, d_in[3]);
    make_scale_map(enc, &maps.vs, d_in[5]);
    make_scale_map(enc, &maps.vz, d_in[6]);

    kv_decode_kernel<<<grid, THREADS, SMEM_BYTES>>>(prm, maps);
}
```

```cpp
#include <cuda_runtime.h>
#include <cuda_bf16.h>
#include <cuda.h>
#include <stdint.h>
#include <type_traits>

namespace {

constexpr int H = 32;
constexpr int S = 16384;
constexpr int D = 192;
constexpr int HALF = D / 2;
constexpr float QK_SCALE = 0.07216878364870322f * 1.4426950408889634f;

constexpr int G = 8;
constexpr int T = 4;
constexpr int TEAMS = H / G;
constexpr int UNITS = S / T;
constexpr int STAGES = 3;
constexpr int TAIL_UNITS = 130;
constexpr int UA = UNITS - TAIL_UNITS;
constexpr int TICKETS = UA + 2 * TAIL_UNITS;
constexpr int F_ROWS = 512;
constexpr int P_ROWS = 64;
constexpr int NP = F_ROWS / P_ROWS;
constexpr int F0 = UA * T - F_ROWS;
constexpr int QUARTERS = 4;
constexpr int QC = D / QUARTERS;
constexpr int FINALIZERS = G * QUARTERS;
constexpr int MAX_CPT = 40;
constexpr int GW = 4;
constexpr int SG = 2 * GW;
constexpr int NSL = MAX_CPT / SG;
constexpr int RSLOTS = 16;
constexpr int RSTRIDE = 52;
constexpr int SLOT_WORDS = QUARTERS * 64;

constexpr int MBOX_STRIDE = 32;
constexpr int PACE_BASE = 290;
constexpr int PACE_DIV = 20700;

constexpr int W_FIN = 1;
constexpr int W_GATHER = 2;
constexpr int W_CONS = W_GATHER + GW;
constexpr int THREADS = (W_CONS + G) * 32;

constexpr int KV_BYTES = G * T * D * 4;
constexpr int ROWS_BYTES = T * D * 4;
constexpr int CS_BYTES = T * D * 2;
constexpr int SC_BYTES = G * 8 * 2;
constexpr int OFF_K = 0;
constexpr int OFF_V = KV_BYTES;
constexpr int OFF_COS = 2 * KV_BYTES;
constexpr int OFF_SIN = OFF_COS + CS_BYTES;
constexpr int OFF_KS = OFF_SIN + CS_BYTES;
constexpr int OFF_KZ = OFF_KS + SC_BYTES;
constexpr int OFF_VS = OFF_KZ + SC_BYTES;
constexpr int OFF_VZ = OFF_VS + SC_BYTES;
constexpr int STAGE_BYTES = OFF_VZ + SC_BYTES;
constexpr int KSIDE_BYTES = STAGE_BYTES - KV_BYTES;
constexpr int PIECE_BYTES = P_ROWS * QC * 4;

constexpr int BAR_FULLK = 0;
constexpr int BAR_FULLV = 8 * STAGES;
constexpr int BAR_EMPTY = 16 * STAGES;
constexpr int BAR_INIT = 24 * STAGES;
constexpr int BAR_END = BAR_INIT + 8;
constexpr int BAR_W = BAR_END + 8;
constexpr int BAR_G = BAR_W + 8;
constexpr int BAR_FIN = BAR_G + 8;
constexpr int OFF_UIDX = 224;
constexpr int OFF_TAG = OFF_UIDX + 4 * STAGES;
constexpr int OFF_TICKET = OFF_TAG + 4;
constexpr int LAST_BIT = 1 << 30;
constexpr int TAG_SHIFT = 29;
constexpr int POS_MASK = (1 << TAG_SHIFT) - 1;
constexpr int CTRL_BYTES = 256;
constexpr int OFF_W = CTRL_BYTES + STAGES * STAGE_BYTES;
constexpr int OFF_RV = OFF_W + F_ROWS * 4;
constexpr int OFF_RG = OFF_RV + RSLOTS * RSTRIDE * 4;
constexpr int SMEM_USED = OFF_W + 2 * KV_BYTES;
static_assert(OFF_RG + SG * RSTRIDE * 4 <= OFF_W + KV_BYTES / 2 && NP <= 2 * STAGES + 2, "final-phase buffers");
static_assert(BAR_FIN + 8 * NP <= OFF_UIDX && OFF_TICKET % 8 == 0, "control block");
constexpr int SMEM_BYTES = SMEM_USED;
static_assert(STAGE_BYTES % 128 == 0 && PIECE_BYTES % 128 == 0 && TEAMS == T, "layout");
static_assert(SMEM_BYTES <= 232448, "shared memory budget");

struct __align__(128) Scratch {
    float part[H * MAX_CPT * SLOT_WORDS];
    uint2 logit[H * F_ROWS];
    unsigned int mbox[H * QUARTERS * MBOX_STRIDE];
    unsigned long long ctr[16];
};
__device__ Scratch g_scratch;

__device__ __forceinline__ uint32_t smem_u32(const void* p) {
    return (uint32_t)__cvta_generic_to_shared(p);
}
__device__ __forceinline__ void mbar_init(uint32_t bar, int cnt) {
    asm volatile("mbarrier.init.shared::cta.b64 [%0], %1;" ::"r"(bar), "r"(cnt) : "memory");
}
__device__ __forceinline__ void mbar_expect_tx(uint32_t bar, uint32_t bytes) {
    asm volatile("mbarrier.arrive.expect_tx.shared::cta.b64 _, [%0], %1;" ::"r"(bar), "r"(bytes) : "memory");
}
__device__ __forceinline__ void mbar_arrive(uint32_t bar) {
    asm volatile("mbarrier.arrive.shared::cta.b64 _, [%0];" ::"r"(bar) : "memory");
}
__device__ __forceinline__ void mbar_wait(uint32_t bar, uint32_t parity) {
    asm volatile(
        "{\n"
        ".reg .pred p;\n"
        ".reg .u32 n;\n"
        "mov.u32 n, 0;\n"
        "WAIT_%=:\n"
        "add.u32 n, n, 1;\n"
        "mbarrier.try_wait.parity.shared::cta.b64 p, [%0], %1;\n"
        "setp.gt.or.u32 p, n, " "0x400000" ", p;\n"
        "@!p bra WAIT_%=;\n"
        "}" ::"r"(bar), "r"(parity) : "memory");
}
__device__ __forceinline__ bool mbar_test(uint32_t bar, uint32_t parity) {
    uint32_t ok;
    asm volatile("{\n.reg .pred p;\nmbarrier.test_wait.parity.shared::cta.b64 p, [%1], %2;\nselp.u32 %0, 1, 0, p;\n}"
                 : "=r"(ok) : "r"(bar), "r"(parity) : "memory");
    return ok != 0;
}
__device__ __forceinline__ uint32_t now_ns() {
    uint32_t t;
    asm volatile("mov.u32 %0, %%globaltimer_lo;" : "=r"(t)::"memory");
    return t;
}
__device__ __forceinline__ bool elect_one() {
    uint32_t p;
    asm volatile("{\n.reg .pred p;\nelect.sync _|p, 0xffffffff;\nselp.u32 %0, 1, 0, p;\n}" : "=r"(p));
    return p != 0;
}
__device__ __forceinline__ void bulk_load(uint32_t dst, const void* src, uint32_t bytes, uint32_t bar) {
    asm volatile("cp.async.bulk.shared::cluster.global.mbarrier::complete_tx::bytes [%0], [%1], %2, [%3];"
                 ::"r"(dst), "l"(src), "r"(bytes), "r"(bar) : "memory");
}
__device__ __forceinline__ void tma3d(uint32_t dst, const CUtensorMap* map, int c0, int c1, int c2,
                                      uint32_t bar, uint64_t pol) {
    asm volatile(
        "cp.async.bulk.tensor.3d.shared::cluster.global.mbarrier::complete_tx::bytes.L2::cache_hint"
        " [%0], [%1, {%2, %3, %4}], [%5], %6;"
        ::"r"(dst), "l"(map), "r"(c0), "r"(c1), "r"(c2), "r"(bar), "l"(pol) : "memory");
}
__device__ __forceinline__ void tma2d(uint32_t dst, const CUtensorMap* map, int c0, int c1, uint32_t bar) {
    asm volatile(
        "cp.async.bulk.tensor.2d.shared::cluster.global.mbarrier::complete_tx::bytes"
        " [%0], [%1, {%2, %3}], [%4];"
        ::"r"(dst), "l"(map), "r"(c0), "r"(c1), "r"(bar) : "memory");
}
__device__ __forceinline__ void prefetch_map(const CUtensorMap* map) {
    asm volatile("prefetch.tensormap [%0];" ::"l"(map) : "memory");
}
__device__ __forceinline__ uint64_t evict_first_policy() {
    uint64_t pol;
    asm volatile("createpolicy.fractional.L2::evict_first.b64 %0, 1.0;" : "=l"(pol));
    return pol;
}
__device__ __forceinline__ float ex2(float x) {
    float y;
    asm("ex2.approx.ftz.f32 %0, %1;" : "=f"(y) : "f"(x));
    return y;
}
__device__ __forceinline__ float bf_lo(uint32_t x) { return __uint_as_float(x << 16); }
__device__ __forceinline__ float bf_hi(uint32_t x) { return __uint_as_float(x & 0xffff0000u); }
__device__ __forceinline__ uint32_t bf2_mul(uint32_t a, uint32_t b) {
    uint32_t d;
    asm("mul.rn.bf16x2 %0, %1, %2;" : "=r"(d) : "r"(a), "r"(b));
    return d;
}
__device__ __forceinline__ uint32_t bf2_add(uint32_t a, uint32_t b) {
    uint32_t d;
    asm("add.rn.bf16x2 %0, %1, %2;" : "=r"(d) : "r"(a), "r"(b));
    return d;
}
__device__ __forceinline__ uint32_t bf2_sub(uint32_t a, uint32_t b) {
    uint32_t d;
    asm("sub.rn.bf16x2 %0, %1, %2;" : "=r"(d) : "r"(a), "r"(b));
    return d;
}
__device__ __forceinline__ float lds_bf16(uint32_t addr) {
    unsigned short v;
    asm volatile("ld.shared.u16 %0, [%1];" : "=h"(v) : "r"(addr));
    return __uint_as_float(((uint32_t)v) << 16);
}
__device__ __forceinline__ int4 lds128(uint32_t addr) {
    int4 v;
    asm volatile("ld.shared.v4.s32 {%0,%1,%2,%3}, [%4];" : "=r"(v.x), "=r"(v.y), "=r"(v.z), "=r"(v.w) : "r"(addr));
    return v;
}
__device__ __forceinline__ uint2 lds64(uint32_t addr) {
    uint2 v;
    asm volatile("ld.shared.v2.u32 {%0,%1}, [%2];" : "=r"(v.x), "=r"(v.y) : "r"(addr));
    return v;
}
__device__ __forceinline__ float2 lds64f(uint32_t addr) {
    const uint2 v = lds64(addr);
    return make_float2(__uint_as_float(v.x), __uint_as_float(v.y));
}
__device__ __forceinline__ uint32_t lds32(uint32_t addr) {
    uint32_t v;
    asm volatile("ld.shared.u32 %0, [%1];" : "=r"(v) : "r"(addr) : "memory");
    return v;
}
__device__ __forceinline__ void sts32(uint32_t addr, uint32_t v) {
    asm volatile("st.shared.u32 [%0], %1;" ::"r"(addr), "r"(v) : "memory");
}
__device__ __forceinline__ void sts128f(uint32_t addr, float a, float b, float c, float d) {
    asm volatile("st.shared.v4.f32 [%0], {%1,%2,%3,%4};" ::"r"(addr), "f"(a), "f"(b), "f"(c), "f"(d) : "memory");
}
__device__ __forceinline__ float warp_max(float x) {
    int k = __float_as_int(x);
    k ^= (k >> 31) & 0x7fffffff;
    k = __reduce_max_sync(0xffffffffu, k);
    return __int_as_float(k ^ ((k >> 31) & 0x7fffffff));
}

__device__ __forceinline__ uint32_t tagged(float x, uint32_t tag) { return (__float_as_uint(x) & ~1u) | tag; }

__device__ __forceinline__ void st_relaxed_b64(const void* p, uint32_t lo, uint32_t hi) {
    asm volatile("{\n.reg .b64 v;\nmov.b64 v, {%1,%2};\nst.relaxed.gpu.global.b64 [%0], v;\n}"
                 ::"l"(p), "r"(lo), "r"(hi) : "memory");
}
template <int OFF>
__device__ __forceinline__ void ld_relaxed_2xb64_if(uint4& v, const void* base, int pred) {
    asm volatile("{\n.reg .pred p;\n.reg .b64 a, b;\nsetp.ne.s32 p, %5, 0;\n"
                 "mov.b64 a, {%0,%1};\nmov.b64 b, {%2,%3};\n"
                 "@p ld.relaxed.gpu.global.v2.b64 {a, b}, [%4+%6];\n"
                 "mov.b64 {%0,%1}, a;\nmov.b64 {%2,%3}, b;\n}"
                 : "+r"(v.x), "+r"(v.y), "+r"(v.z), "+r"(v.w) : "l"(base), "r"(pred), "n"(OFF) : "memory");
}
__device__ __forceinline__ void mbox_post(unsigned int* box, unsigned int bits) {
    asm volatile("red.relaxed.gpu.global.add.u32 [%0], %1;" ::"l"(box), "r"(bits) : "memory");
}
__device__ __forceinline__ unsigned int mbox_take(unsigned int* box) {
    unsigned int v;
    asm volatile("atom.relaxed.gpu.global.exch.b32 %0, [%1], 0;" : "=r"(v) : "l"(box) : "memory");
    return v;
}
template <int OFF>
__device__ __forceinline__ uint2 ldg64(const void* base) {
    uint2 v;
    asm volatile("ld.global.nc.v2.u32 {%0,%1}, [%2+%3];" : "=r"(v.x), "=r"(v.y) : "l"(base), "n"(OFF));
    return v;
}
template <int N, typename F>
__device__ __forceinline__ void static_for(F&& f) {
    if constexpr (N > 0) {
        static_for<N - 1>(f);
        f(std::integral_constant<int, N - 1>{});
    }
}
__device__ __forceinline__ unsigned long long draw(unsigned long long* ctr, unsigned long long inc) {
    unsigned long long v;
    asm volatile("atom.relaxed.gpu.global.add.u64 %0, [%1], %2;" : "=l"(v) : "l"(ctr), "l"(inc) : "memory");
    return v;
}

__device__ __forceinline__ uint32_t piece_off(int p) {
    return CTRL_BYTES + KV_BYTES / 2 + (p >> 1) * STAGE_BYTES + (p & 1) * KV_BYTES;
}
static_assert(PIECE_BYTES == KV_BYTES / 2 && OFF_K == 0 && OFF_V == KV_BYTES, "piece placement");

struct Params {
    const int* qk;
    const __nv_bfloat16* k_cos;
    const __nv_bfloat16* k_sin;
    Scratch* scratch;
    const __nv_bfloat16* q;
    const __nv_bfloat16* q_cos;
    const __nv_bfloat16* q_sin;
    __nv_bfloat16* out;
};
struct Maps {
    CUtensorMap k, v, ks, kz, vs, vz, kh, vh, vf;
};

__global__ void __launch_bounds__(THREADS, 1)
kv_decode_kernel(const __grid_constant__ Params prm, const __grid_constant__ Maps maps) {
    extern __shared__ __align__(1024) unsigned char smem[];
    if (threadIdx.x < 32 && elect_one()) {
        const uint32_t sb = smem_u32(smem);
        mbar_init(sb + BAR_FULLK, 1);
        asm volatile("fence.mbarrier_init.release.cluster;" ::: "memory");
        const uint32_t row = (blockIdx.x % TEAMS) * (G * S - 1) + blockIdx.x;
        const char* src = reinterpret_cast<const char*>(prm.qk) + row * (size_t)(D * 4);
        uint32_t dst = sb + CTRL_BYTES;
#pragma unroll 1
        do {
            bulk_load(dst, src, ROWS_BYTES, sb + BAR_FULLK);
            dst += ROWS_BYTES;
            src += S * D * 4;
        } while (dst != sb + CTRL_BYTES + KV_BYTES);
#pragma unroll
        for (int i = 1; i < BAR_FIN / 8 + NP; i++) mbar_init(sb + 8 * i, (unsigned)(i - BAR_EMPTY / 8) < STAGES ? G : 1);
        asm volatile("fence.mbarrier_init.release.cluster;" ::: "memory");
    }

    uint32_t bid;
    asm volatile("mov.u32 %0, %%ctaid.x;" : "=r"(bid));
    const int team = bid % TEAMS;
    const int cin = bid / TEAMS;
    const int h0 = team * G;
    const uint32_t sb = __shfl_sync(0xffffffffu, smem_u32(smem), 0);
    const uint32_t buf0 = sb + CTRL_BYTES;
    const int warp = __shfl_sync(0xffffffffu, threadIdx.x >> 5, 0);
    const int lane = threadIdx.x & 31;
    const int cpt = gridDim.x / TEAMS;

    if (warp >= W_CONS) {
        const int cw = warp - W_CONS;
        const int h = h0 + cw;
        const int r = lane >> 3;
        const int j = lane & 7;

        float qa[3][4], qb[3][4];
        {
            const __nv_bfloat16* qp = prm.q + h * D + 4 * j;
            const __nv_bfloat16* cp = prm.q_cos + 4 * j;
            const __nv_bfloat16* sp = prm.q_sin + 4 * j;
            static_for<3>([&](auto ic) {
                constexpr int i = decltype(ic)::value;
                const uint2 x1 = ldg64<64 * i>(qp), x2 = ldg64<64 * i + 2 * HALF>(qp);
                const uint2 c1 = ldg64<64 * i>(cp), c2 = ldg64<64 * i + 2 * HALF>(cp);
                const uint2 s1 = ldg64<64 * i>(sp), s2 = ldg64<64 * i + 2 * HALF>(sp);
                const uint32_t a0 = bf2_sub(bf2_mul(x1.x, c1.x), bf2_mul(x2.x, s1.x));
                const uint32_t a1 = bf2_sub(bf2_mul(x1.y, c1.y), bf2_mul(x2.y, s1.y));
                const uint32_t b0 = bf2_add(bf2_mul(x2.x, c2.x), bf2_mul(x1.x, s2.x));
                const uint32_t b1 = bf2_add(bf2_mul(x2.y, c2.y), bf2_mul(x1.y, s2.y));
                qa[i][0] = bf_lo(a0); qa[i][1] = bf_hi(a0); qa[i][2] = bf_lo(a1); qa[i][3] = bf_hi(a1);
                qb[i][0] = bf_lo(b0); qb[i][1] = bf_hi(b0); qb[i][2] = bf_lo(b1); qb[i][3] = bf_hi(b1);
            });
        }
        float acc[6][4];
#pragma unroll
        for (int i = 0; i < 6; i++)
#pragma unroll
            for (int c = 0; c < 4; c++) acc[i][c] = 0.f;
        float m_run = -3e38f, l_run = 0.f;
        float z_run = 0.f;

        const uint32_t va_off = OFF_V + ((lane & 16) ? 384 : 0);
        const uint32_t vb_off = OFF_V + ((lane & 16) ? 0 : 384);
        uint32_t kv_off = (uint32_t)((cw * T + r) * (D * 4) + j * 16);
        uint32_t cs_off = (uint32_t)(OFF_COS + r * (D * 2) + j * 8);
        uint32_t sc_off = (uint32_t)(OFF_KS + cw * 16 + r * 2);
        float mask = 0.f;

        asm volatile("bar.sync 0, %0;" ::"n"(THREADS) : "memory");

        int s = 0, word;
        uint32_t ph = 0;
#pragma unroll 1
        do {
            mbar_wait(sb + BAR_FULLK + 8 * s, ph);
            word = (int)lds32(sb + OFF_UIDX + 4 * s);
            const int pos = word & POS_MASK;
            if (pos >= UA * T) {
                kv_off = (uint32_t)((cw * (T / 2) + (r & 1)) * (D * 4) + j * 16);
                cs_off = (uint32_t)(OFF_COS + (r & 1) * (D * 2) + j * 8);
                sc_off = (uint32_t)(OFF_KS + cw * 16 + (r & 1) * 2);
                mask = r >= 2 ? -INFINITY : 0.f;
            }
            const uint32_t st = buf0 + s * STAGE_BYTES;
            const uint32_t sc = st + sc_off + (pos & 7) * 2;
            const float kz = lds_bf16(sc + SC_BYTES);
            const float ks = lds_bf16(sc) * QK_SCALE;
            const float vs = lds_bf16(sc + 2 * SC_BYTES);
            const float vz = lds_bf16(sc + 3 * SC_BYTES);

            float d0 = 0.f, d1 = 0.f;
#pragma unroll
            for (int i = 0; i < 3; i++) {
                const int4 ka = lds128(st + kv_off + i * 128);
                const int4 kb = lds128(st + kv_off + (i + 3) * 128);
                const uint2 ca = lds64(st + cs_off + i * 64);
                const uint2 cb = lds64(st + cs_off + (i + 3) * 64);
                const uint2 sa = lds64(st + cs_off + CS_BYTES + i * 64);
                const uint2 sb2 = lds64(st + cs_off + CS_BYTES + (i + 3) * 64);
                const float a[4] = {(float)ka.x - kz, (float)ka.y - kz, (float)ka.z - kz, (float)ka.w - kz};
                const float b[4] = {(float)kb.x - kz, (float)kb.y - kz, (float)kb.z - kz, (float)kb.w - kz};
                const float fca[4] = {bf_lo(ca.x), bf_hi(ca.x), bf_lo(ca.y), bf_hi(ca.y)};
                const float fcb[4] = {bf_lo(cb.x), bf_hi(cb.x), bf_lo(cb.y), bf_hi(cb.y)};
                const float fsa[4] = {bf_lo(sa.x), bf_hi(sa.x), bf_lo(sa.y), bf_hi(sa.y)};
                const float fsb[4] = {bf_lo(sb2.x), bf_hi(sb2.x), bf_lo(sb2.y), bf_hi(sb2.y)};
#pragma unroll
                for (int c = 0; c < 4; c++) {
                    const float ra = fmaf(a[c], fca[c], -b[c] * fsa[c]);
                    const float rb = fmaf(b[c], fcb[c], a[c] * fsb[c]);
                    d0 = fmaf(qa[i][c], ra, d0);
                    d1 = fmaf(qb[i][c], rb, d1);
                }
            }
            float dot = d0 + d1;
            dot += __shfl_xor_sync(0xffffffffu, dot, 1);
            dot += __shfl_xor_sync(0xffffffffu, dot, 2);
            dot += __shfl_xor_sync(0xffffffffu, dot, 4);
            const float sv = dot * ks;

            if ((unsigned)(pos - F0) < (unsigned)F_ROWS) {
                if (j == 0)
                    st_relaxed_b64(prm.scratch->logit + h * F_ROWS + (pos - F0) + r,
                                   (__float_as_uint(vs) >> 16) | __float_as_uint(vz),
                                   tagged(fmaxf(sv, -3e38f), (word >> TAG_SHIFT) & 1));
            } else {
                if (__any_sync(0xffffffffu, sv > m_run)) {
                    float m_new = fmaxf(sv, __shfl_xor_sync(0xffffffffu, sv, 8));
                    m_new = fmaxf(m_run, fmaxf(m_new, __shfl_xor_sync(0xffffffffu, m_new, 16)));
                    const float alpha = ex2(m_run - m_new);
                    l_run *= alpha;
                    z_run *= alpha;
#pragma unroll
                    for (int i = 0; i < 6; i++)
#pragma unroll
                        for (int c = 0; c < 4; c++) acc[i][c] *= alpha;
                    m_run = m_new;
                }
                const float p = ex2(sv - m_run + mask);
                const float pv = p * vs;
                l_run += p;
                z_run = fmaf(pv, vz, z_run);
                mbar_wait(sb + BAR_FULLV + 8 * s, ph);
#pragma unroll
                for (int i = 0; i < 6; i++) {
                    const int4 v = lds128(st + kv_off + (i < 3 ? va_off : vb_off) + (i % 3) * 128);
                    acc[i][0] = fmaf(pv, (float)v.x, acc[i][0]);
                    acc[i][1] = fmaf(pv, (float)v.y, acc[i][1]);
                    acc[i][2] = fmaf(pv, (float)v.z, acc[i][2]);
                    acc[i][3] = fmaf(pv, (float)v.w, acc[i][3]);
                }
            }
            __syncwarp();
            if (lane == 0) mbar_arrive(sb + BAR_EMPTY + 8 * s);
            if (++s == STAGES) { s = 0; ph ^= 1; }
        } while (!(word & LAST_BIT));

        {
            const uint32_t tag = (word >> TAG_SHIFT) & 1;
            char* slot = reinterpret_cast<char*>(prm.scratch->part + (h * MAX_CPT + cin) * SLOT_WORDS);
            char* part_st = slot + (lane & 16) * 32 + j * 16 + (lane & 8);
            l_run += __shfl_xor_sync(0xffffffffu, l_run, 8);
            z_run += __shfl_xor_sync(0xffffffffu, z_run, 8);
            l_run += __shfl_xor_sync(0xffffffffu, l_run, 16);
            z_run += __shfl_xor_sync(0xffffffffu, z_run, 16);
            st_relaxed_b64(slot + r * 256 + QC * 4 + j * 8, __float_as_uint(m_run), tagged(l_run, tag));
            const bool od = (lane & 8) != 0;
#pragma unroll
            for (int i = 0; i < 3; i++) {
                float k[4];
#pragma unroll
                for (int c = 0; c < 4; c++) k[c] = acc[i][c] + __shfl_xor_sync(0xffffffffu, acc[i + 3][c], 16);
                const float z0 = (od ? k[2] : k[0]) + __shfl_xor_sync(0xffffffffu, od ? k[0] : k[2], 8);
                const float z1 = (od ? k[3] : k[1]) + __shfl_xor_sync(0xffffffffu, od ? k[1] : k[3], 8);
                st_relaxed_b64(part_st + i * 128 + (i == 2 ? 64 : i == 1 ? (j & 4) * 16 : 0),
                               __float_as_uint(z0 - z_run), tagged(z1 - z_run, tag));
            }
            if (lane < QUARTERS) mbox_post(prm.scratch->mbox + (h * QUARTERS + lane) * MBOX_STRIDE, 1u);
        }

        if (cin >= FINALIZERS || cw >= RSLOTS * 12 / 32) return;
        const int ft = threadIdx.x - W_CONS * 32;
        const int rs = ft / 12;
        float a0 = 0.f, a1 = 0.f, a2 = 0.f, a3 = 0.f;
        mbar_wait(sb + BAR_W, 0);
        const uint32_t ra = sb + OFF_RV + rs * (RSTRIDE * 4 - QC * 4) + ft * 16;
#pragma unroll 1
        for (int p = 0; p < NP; p++) {
            const int4 w4 = lds128(sb + OFF_W + p * (P_ROWS * 4) + rs * 16);
            const float w[4] = {__int_as_float(w4.x), __int_as_float(w4.y), __int_as_float(w4.z), __int_as_float(w4.w)};
            const uint32_t va = sb + piece_off(p) + ft * 16;
            mbar_wait(sb + BAR_FIN + 8 * p, 0);
#pragma unroll
            for (int i = 0; i < 4; i++) {
                const int4 v = lds128(va + i * (RSLOTS * QC * 4));
                a0 = fmaf(w[i], (float)v.x, a0);
                a1 = fmaf(w[i], (float)v.y, a1);
                a2 = fmaf(w[i], (float)v.z, a2);
                a3 = fmaf(w[i], (float)v.w, a3);
            }
        }
        sts128f(ra, a0, a1, a2, a3);
        asm volatile("bar.arrive 3, %0;" ::"n"(RSLOTS * 12 + 32) : "memory");
        return;
    }

    if (warp >= W_GATHER) {
        asm volatile("bar.sync 0, %0;" ::"n"(THREADS) : "memory");
        if (cin >= FINALIZERS) return;
        const int sub = lane >= 13, quad = min(lane - sub * 13, 12);
        const int sg = 2 * (warp - W_GATHER) + sub;
        const float* src = prm.scratch->part + ((h0 + cin / QUARTERS) * MAX_CPT + sg) * SLOT_WORDS +
                           (cin % QUARTERS) * 64 + quad * 4;
        uint4 dt[NSL];
        unsigned need = 0;
#pragma unroll
        for (int b = 0; b < NSL; b++) {
            dt[b] = make_uint4(quad == 12 ? 0xff800000u : 0u, 0u, 0u, 0u);
            if (sg + b * SG < cpt) need |= 1u << b;
        }
        mbar_wait(sb + BAR_INIT, 0);
        const uint32_t tag = lds32(sb + OFF_TAG);
        mbar_wait(sb + BAR_G, 0);
        int spin = 0;
#pragma unroll 1
        do {
            static_for<NSL>([&](auto bc) {
                constexpr int b = decltype(bc)::value;
                ld_relaxed_2xb64_if<b * SG * SLOT_WORDS * 4>(dt[b], src, need & (1u << b));
            });
            unsigned bad = 0;
#pragma unroll
            for (int b = 0; b < NSL; b++) bad |= (((dt[b].y ^ tag) | (dt[b].w ^ tag)) & 1u) << b;
            need &= bad;
        } while (__any_sync(0xffffffffu, need) && ++spin < (1 << 20));
        float mh[NSL], m = -INFINITY;
#pragma unroll
        for (int b = 0; b < NSL; b++) {
            mh[b] = __shfl_sync(0xffffffffu, __uint_as_float(dt[b].x), sub * 13 + 12);
            m = fmaxf(m, mh[b]);
        }
        float a0 = 0.f, a1 = 0.f, a2 = 0.f, a3 = 0.f;
#pragma unroll
        for (int b = 0; b < NSL; b++) {
            const float w = ex2(mh[b] - m);
            a0 = fmaf(w, __uint_as_float(dt[b].x), a0);
            a1 = fmaf(w, __uint_as_float(dt[b].y), a1);
            a2 = fmaf(w, __uint_as_float(dt[b].z), a2);
            a3 = fmaf(w, __uint_as_float(dt[b].w), a3);
        }
        if (lane < 26) sts128f(sb + OFF_RG + sg * (RSTRIDE * 4) + quad * 16, quad == 12 ? m : a0, a1, a2, a3);
        asm volatile("bar.arrive 2, %0;" ::"n"(GW * 32 + 32) : "memory");
        return;
    }

    if (warp == W_FIN) {
        if (elect_one()) {
            prefetch_map(&maps.ks);
            prefetch_map(&maps.kz);
            prefetch_map(&maps.vs);
            prefetch_map(&maps.vz);
            prefetch_map(&maps.k);
            prefetch_map(&maps.v);
        }
        asm volatile("bar.sync 0, %0;" ::"n"(THREADS) : "memory");
        if (cin >= FINALIZERS) return;
        const char* lptr = reinterpret_cast<const char*>(prm.scratch->logit + (h0 + cin / QUARTERS) * F_ROWS) + lane * 16;
        __nv_bfloat16* optr = prm.out + h0 * D + cin * QC + 2 * lane;
        mbar_wait(sb + BAR_INIT, 0);
        const uint32_t tag = lds32(sb + OFF_TAG);
        uint4 rec[NP];
        bool ok;
        int spin = 0;
        do {
            static_for<NP>([&](auto ic) { ld_relaxed_2xb64_if<decltype(ic)::value * 512>(rec[decltype(ic)::value], lptr, 1); });
            uint32_t bad = 0;
#pragma unroll
            for (int i = 0; i < NP; i++) bad |= (rec[i].y ^ tag) | (rec[i].w ^ tag);
            ok = (bad & 1u) == 0;
        } while (!__all_sync(0xffffffffu, ok) && ++spin < (1 << 20));
        float mF = -INFINITY, lF = 0.f, zF = 0.f;
#pragma unroll
        for (int i = 0; i < NP; i++) mF = fmaxf(mF, fmaxf(__uint_as_float(rec[i].y), __uint_as_float(rec[i].w)));
        mF = warp_max(mF);
        const uint32_t wa = sb + OFF_W + (lane & 7) * 32 + (lane >> 3) * 4;
#pragma unroll
        for (int i = 0; i < NP; i++) {
            const float p0 = ex2(__uint_as_float(rec[i].y) - mF), p1 = ex2(__uint_as_float(rec[i].w) - mF);
            const float a0 = p0 * bf_lo(rec[i].x), a1 = p1 * bf_lo(rec[i].z);
            lF += p0 + p1;
            zF = fmaf(a0, bf_hi(rec[i].x), fmaf(a1, bf_hi(rec[i].z), zF));
            sts32(wa + i * (P_ROWS * 4), __float_as_uint(a0));
            sts32(wa + i * (P_ROWS * 4) + 16, __float_as_uint(a1));
        }
        __syncwarp();
        if (lane == 0) mbar_arrive(sb + BAR_W);
#pragma unroll
        for (int o = 16; o > 0; o >>= 1) {
            lF += __shfl_xor_sync(0xffffffffu, lF, o);
            zF += __shfl_xor_sync(0xffffffffu, zF, o);
        }
        mbar_wait(sb + BAR_END, 0);
        if (lane == 0) {
            unsigned int* box = prm.scratch->mbox + (h0 * QUARTERS + cin) * MBOX_STRIDE;
            int seen = 0;
            do seen += mbox_take(box); while (seen < cpt && ++spin < (1 << 20));
            mbar_arrive(sb + BAR_G);
        }
        __syncwarp();
        const uint32_t col = sb + (uint32_t)min(lane, QC / 2 - 1) * 8;
        asm volatile("bar.sync 2, %0;" ::"r"(__float_as_uint(lF + zF) == 0xffffffffu ? 32 : GW * 32 + 32) : "memory");
        float2 ml[SG], ga[SG];
#pragma unroll
        for (int g = 0; g < SG; g++) {
            ml[g] = lds64f(sb + OFF_RG + g * (RSTRIDE * 4) + QC * 4);
            ga[g] = lds64f(col + OFF_RG + g * (RSTRIDE * 4));
        }
        float M = mF;
#pragma unroll
        for (int g = 0; g < SG; g++) M = fmaxf(M, ml[g].x);
        float wF = ex2(mF - M);
        float L = wF * lF, b0 = -wF * zF, b1 = b0;
#pragma unroll
        for (int g = 0; g < SG; g++) {
            const float w = ex2(ml[g].x - M);
            L = fmaf(w, ml[g].y, L);
            b0 = fmaf(w, ga[g].x, b0);
            b1 = fmaf(w, ga[g].y, b1);
        }
        const float inv = __fdividef(1.f, L);
        wF *= inv;
        b0 *= inv;
        b1 *= inv;
        asm volatile("bar.sync 3, %0;"
                     ::"r"(__any_sync(0xffffffffu, __float_as_uint(wF + b0 + b1) == 0xffffffffu) ? 32 : RSLOTS * 12 + 32) : "memory");
        float2 rv[RSLOTS];
#pragma unroll
        for (int g = 0; g < RSLOTS; g++) rv[g] = lds64f(col + OFF_RV + g * (RSTRIDE * 4));
        static_for<4>([&](auto lc) {
            constexpr int o = RSLOTS / 2 >> decltype(lc)::value;
#pragma unroll
            for (int g = 0; g < o; g++) {
                rv[g].x += rv[g + o].x;
                rv[g].y += rv[g + o].y;
            }
        });
        if (lane < QC / 2)
            *reinterpret_cast<__nv_bfloat162*>(optr) = __floats2bfloat162_rn(fmaf(wF, rv[0].x, b0), fmaf(wF, rv[0].y, b1));
        return;
    }

    __syncwarp();
    asm volatile("bar.arrive 0, %0;" ::"n"(THREADS) : "memory");
    if (!elect_one()) return;
    const uint64_t pol = evict_first_policy();
    unsigned long long* ctr = prm.scratch->ctr;
    const int total = TICKETS - (STAGES - 1) * cpt;
    const unsigned long long inc = 1ull << (15 * team);
    unsigned long long ticket = draw(ctr, inc);
    const uint32_t t_begin = now_ns();
    uint32_t w1 = 0, w2 = 0, w3 = 0;
    auto push = [&](uint32_t w) { w3 = w2; w2 = w1; w1 = w; };
    int s = 0, u = cin, k = 0, halves = 0, drawn = 0;
    uint32_t ph = 0;
    uint32_t t_draw = 0;
    bool init_done = false;
#pragma unroll 1
    for (;; k++) {
        const bool half = u >= UA;
        const int pos = half ? (u + UA) * (T / 2) : u * T;
        const int p8 = pos & ~7;
        const uint32_t fb = sb + BAR_FULLK + 8 * s;
        const uint32_t fv = sb + BAR_FULLV + 8 * s;
        const uint32_t dst = buf0 + s * STAGE_BYTES;
        halves += half;
        const bool gated = k >= STAGES && halves < STAGES;
        mbar_wait(sb + BAR_EMPTY + 8 * s, ph ^ 1);
        if (gated) mbar_wait(w3 & ~1u, w3 & 1u);
        if (k > 0) tma3d(dst + OFF_K, half ? &maps.kh : &maps.k, 0, pos, h0, fb, pol);
        bulk_load(dst + OFF_COS, prm.k_cos + (size_t)pos * D, half ? CS_BYTES / 2 : CS_BYTES, fb);
        bulk_load(dst + OFF_SIN, prm.k_sin + (size_t)pos * D, half ? CS_BYTES / 2 : CS_BYTES, fb);
        tma2d(dst + OFF_KS, &maps.ks, p8, h0, fb);
        tma2d(dst + OFF_KZ, &maps.kz, p8, h0, fb);
        tma2d(dst + OFF_VS, &maps.vs, p8, h0, fb);
        tma2d(dst + OFF_VZ, &maps.vz, p8, h0, fb);
        if (k >= STAGES) ticket = draw(ctr, inc);
        if (half) t_draw = now_ns();
        push(fb | ph);
        if ((unsigned)(pos - F0) < (unsigned)F_ROWS) {
            mbar_arrive(fv);
            prefetch_map(&maps.kh);
            prefetch_map(&maps.vh);
            prefetch_map(&maps.vf);
        } else {
            if (gated) mbar_wait(w3 & ~1u, w3 & 1u);
            mbar_expect_tx(fv, half ? KV_BYTES / 2 : KV_BYTES);
            tma3d(dst + OFF_V, half ? &maps.vh : &maps.v, 0, pos, h0, fv, pol);
            push(fv | ph);
        }
        int un = u + cpt;
        uint32_t tag = 0;
        if (k >= STAGES - 1) {
            uint32_t lo, hi;
            asm volatile("st.shared.b64 [%2], %3;\nld.volatile.shared.v2.u32 {%0,%1}, [%2];"
                         : "=r"(lo), "=r"(hi) : "r"(sb + OFF_TICKET), "l"(ticket) : "memory");
            const int t01 = (int)(lo & 0x3fffffff), t23 = (int)(__funnelshift_r(lo, hi, 30) & 0x3fffffff);
            const int t = ((team & 2 ? t23 : t01) >> (15 * (team & 1))) & 0x7fff;
            drawn = (t01 & 0x7fff) + (t01 >> 15) + (t23 & 0x7fff) + (t23 >> 15);
            tag = ~hi >> 31;
            un = STAGES * cpt + t;
        }
        const bool start_fin = !init_done && un >= TICKETS - 2 * cpt;
        init_done |= start_fin;
        sts32(sb + OFF_UIDX + 4 * s, pos | (tag << TAG_SHIFT) | (un >= TICKETS ? LAST_BIT : 0));
        mbar_expect_tx(fb, half ? KSIDE_BYTES - KV_BYTES / 2 - CS_BYTES : KSIDE_BYTES);
        if (start_fin) {
            sts32(sb + OFF_TAG, tag);
            mbar_arrive(sb + BAR_INIT);
        }
        if (un >= TICKETS) break;
        u = un;
        if (++s == STAGES) { s = 0; ph ^= 1; }
    }
    mbar_arrive(sb + BAR_END);
    if (drawn == TEAMS * total - 1) draw(ctr, (1ull << 63) - total * 0x0000200040008001ull);
    if (cin >= FINALIZERS) return;
    uint32_t t_next = now_ns();
    int dt = (int)(t_draw - t_next) +
             (int)(((t_draw - t_begin) >> 4) * (uint32_t)(PACE_BASE + min(TEAMS * total - drawn, 512)) / (PACE_DIV / 16));
    dt = max(dt, 0) / NP;
    if (halves < STAGES) {
        mbar_wait(sb + BAR_EMPTY + 8 * s, ph);
        dt = 0;
    }
#pragma unroll 1
    for (int p = 0; p < NP; p++) {
        const uint32_t fb = sb + BAR_FIN + 8 * p;
        t_next += dt;
        while ((int)(now_ns() - t_next) < 0 && !mbar_test(w2 & ~1u, w2 & 1u)) {}
        mbar_expect_tx(fb, PIECE_BYTES);
        tma3d(sb + piece_off(p), &maps.vf, (cin % QUARTERS) * QC, F0 + p * P_ROWS, h0 + cin / QUARTERS, fb, pol);
        push(fb);
    }
}

__global__ void __launch_bounds__(128)
fallback_partial_kernel(const Params prm, const int* qv, const __nv_bfloat16* ks, const __nv_bfloat16* kz,
                        const __nv_bfloat16* vs, const __nv_bfloat16* vz) {
    const int h = blockIdx.y, slot = blockIdx.x * 4 + (threadIdx.x >> 5), lane = threadIdx.x & 31;
    float qa[3], qb[3], acc[6] = {0.f, 0.f, 0.f, 0.f, 0.f, 0.f};
    for (int i = 0; i < 3; i++) {
        const int d = 32 * i + lane;
        const __nv_bfloat16 x1 = prm.q[h * D + d], x2 = prm.q[h * D + d + HALF];
        qa[i] = __bfloat162float(__hsub_rn(__hmul_rn(x1, prm.q_cos[d]), __hmul_rn(x2, prm.q_sin[d])));
        qb[i] = __bfloat162float(__hadd_rn(__hmul_rn(x2, prm.q_cos[d + HALF]), __hmul_rn(x1, prm.q_sin[d + HALF])));
    }
    float m = -3e38f, l = 0.f;
    for (int pos = slot; pos < S; pos += MAX_CPT) {
        const size_t row = (size_t)h * S + pos;
        const float z = __bfloat162float(kz[row]);
        float dot = 0.f;
        for (int i = 0; i < 3; i++) {
            const int d = 32 * i + lane;
            const float a = (float)prm.qk[row * D + d] - z, b = (float)prm.qk[row * D + d + HALF] - z;
            const __nv_bfloat16* c = prm.k_cos + pos * D + d;
            const __nv_bfloat16* sn = prm.k_sin + pos * D + d;
            dot += qa[i] * (a * __bfloat162float(c[0]) - b * __bfloat162float(sn[0])) +
                   qb[i] * (b * __bfloat162float(c[HALF]) + a * __bfloat162float(sn[HALF]));
        }
        for (int o = 16; o > 0; o >>= 1) dot += __shfl_xor_sync(0xffffffffu, dot, o);
        const float sv = dot * __bfloat162float(ks[row]) * QK_SCALE;
        const float m_new = fmaxf(m, sv), alpha = ex2(m - m_new), p = ex2(sv - m_new);
        const float pv = p * __bfloat162float(vs[row]), zv = __bfloat162float(vz[row]);
        m = m_new;
        l = l * alpha + p;
        for (int i = 0; i < 6; i++) acc[i] = acc[i] * alpha + pv * ((float)qv[row * D + 32 * i + lane] - zv);
    }
    float* dst = prm.scratch->part + (h * MAX_CPT + slot) * SLOT_WORDS;
    for (int i = 0; i < 6; i++) dst[32 * i + lane] = acc[i];
    if (lane == 0) {
        dst[D] = m;
        dst[D + 1] = l;
    }
}

__global__ void __launch_bounds__(D) fallback_merge_kernel(const Params prm) {
    const float* src = prm.scratch->part + blockIdx.x * MAX_CPT * SLOT_WORDS;
    float m = -3e38f, l = 0.f, o = 0.f;
    for (int c = 0; c < MAX_CPT; c++) m = fmaxf(m, src[c * SLOT_WORDS + D]);
    for (int c = 0; c < MAX_CPT; c++) {
        const float w = ex2(src[c * SLOT_WORDS + D] - m);
        l += w * src[c * SLOT_WORDS + D + 1];
        o += w * src[c * SLOT_WORDS + threadIdx.x];
    }
    prm.out[blockIdx.x * D + threadIdx.x] = __float2bfloat16_rn(o / l);
}

typedef CUresult (*EncodeTiledFn)(CUtensorMap*, CUtensorMapDataType, cuuint32_t, void*, const cuuint64_t*,
                                  const cuuint64_t*, const cuuint32_t*, const cuuint32_t*,
                                  CUtensorMapInterleave, CUtensorMapSwizzle, CUtensorMapL2promotion,
                                  CUtensorMapFloatOOBfill);

void make_kv_map(EncodeTiledFn enc, CUtensorMap* m, const void* ptr, int cols, int rows, int heads,
                 CUtensorMapL2promotion promo) {
    cuuint64_t dims[3] = {(cuuint64_t)D, (cuuint64_t)S, (cuuint64_t)H};
    cuuint64_t strides[2] = {(cuuint64_t)D * 4, (cuuint64_t)S * D * 4};
    cuuint32_t box[3] = {(cuuint32_t)cols, (cuuint32_t)rows, (cuuint32_t)heads};
    cuuint32_t es[3] = {1, 1, 1};
    enc(m, CU_TENSOR_MAP_DATA_TYPE_INT32, 3, const_cast<void*>(ptr), dims, strides, box, es,
        CU_TENSOR_MAP_INTERLEAVE_NONE, CU_TENSOR_MAP_SWIZZLE_NONE, promo, CU_TENSOR_MAP_FLOAT_OOB_FILL_NONE);
}

void make_scale_map(EncodeTiledFn enc, CUtensorMap* m, const void* ptr) {
    cuuint64_t dims[2] = {(cuuint64_t)S, (cuuint64_t)H};
    cuuint64_t strides[1] = {(cuuint64_t)S * 2};
    cuuint32_t box[2] = {8, (cuuint32_t)G};
    cuuint32_t es[2] = {1, 1};
    enc(m, CU_TENSOR_MAP_DATA_TYPE_BFLOAT16, 2, const_cast<void*>(ptr), dims, strides, box, es,
        CU_TENSOR_MAP_INTERLEAVE_NONE, CU_TENSOR_MAP_SWIZZLE_NONE, CU_TENSOR_MAP_L2_PROMOTION_NONE,
        CU_TENSOR_MAP_FLOAT_OOB_FILL_NONE);
}

}

extern "C" void kernel_launch(void* const* d_in, const int* in_sizes, int n_in, void* d_out, int out_size) {
    (void)in_sizes; (void)n_in; (void)out_size;
    static EncodeTiledFn enc = nullptr;
    static Scratch* scratch = nullptr;
    static int grid = 0;
    if (!enc) {
        void* fn = nullptr;
        cudaDriverEntryPointQueryResult qr;
        cudaGetDriverEntryPoint("cuTensorMapEncodeTiled", &fn, cudaEnableDefault, &qr);
        enc = (EncodeTiledFn)fn;
        int dev = 0, sms = 0;
        cudaGetDevice(&dev);
        cudaDeviceGetAttribute(&sms, cudaDevAttrMultiProcessorCount, dev);
        int cpt = sms / TEAMS;
        if (cpt > MAX_CPT) cpt = MAX_CPT;
        grid = cpt * TEAMS;
        cudaGetSymbolAddress((void**)&scratch, g_scratch);
        cudaFuncSetAttribute(kv_decode_kernel, cudaFuncAttributeMaxDynamicSharedMemorySize, SMEM_BYTES);
    }
    Params prm;
    prm.q = (const __nv_bfloat16*)d_in[0];
    prm.qk = (const int*)d_in[1];
    prm.q_cos = (const __nv_bfloat16*)d_in[7];
    prm.q_sin = (const __nv_bfloat16*)d_in[8];
    prm.k_cos = (const __nv_bfloat16*)d_in[9];
    prm.k_sin = (const __nv_bfloat16*)d_in[10];
    prm.out = (__nv_bfloat16*)d_out;
    prm.scratch = scratch;
    if (grid < TEAMS * FINALIZERS) {
        fallback_partial_kernel<<<dim3(MAX_CPT / 4, H), 128>>>(
            prm, (const int*)d_in[4], (const __nv_bfloat16*)d_in[2], (const __nv_bfloat16*)d_in[3],
            (const __nv_bfloat16*)d_in[5], (const __nv_bfloat16*)d_in[6]);
        fallback_merge_kernel<<<H, D>>>(prm);
        return;
    }
    Maps maps;
    make_kv_map(enc, &maps.k, prm.qk, D, T, G, CU_TENSOR_MAP_L2_PROMOTION_L2_128B);
    make_kv_map(enc, &maps.v, d_in[4], D, T, G, CU_TENSOR_MAP_L2_PROMOTION_L2_128B);
    make_kv_map(enc, &maps.kh, prm.qk, D, T / 2, G, CU_TENSOR_MAP_L2_PROMOTION_L2_128B);
    make_kv_map(enc, &maps.vh, d_in[4], D, T / 2, G, CU_TENSOR_MAP_L2_PROMOTION_L2_128B);
    make_kv_map(enc, &maps.vf, d_in[4], QC, P_ROWS, 1, CU_TENSOR_MAP_L2_PROMOTION_NONE);
    make_scale_map(enc, &maps.ks, d_in[2]);
    make_scale_map(enc, &maps.kz, d_in[3]);
    make_scale_map(enc, &maps.vs, d_in[5]);
    make_scale_map(enc, &maps.vz, d_in[6]);

    kv_decode_kernel<<<grid, THREADS, SMEM_BYTES>>>(prm, maps);
}
```

```cpp
#include <cuda_runtime.h>
#include <cuda_bf16.h>
#include <cuda.h>
#include <stdint.h>
#include <type_traits>

namespace {

constexpr int H = 32;
constexpr int S = 16384;
constexpr int D = 192;
constexpr int HALF = D / 2;
constexpr float QK_SCALE = 0.07216878364870322f * 1.4426950408889634f;

constexpr int G = 8;
constexpr int T = 4;
constexpr int TEAMS = H / G;
constexpr int UNITS = S / T;
constexpr int STAGES = 3;
constexpr int TAIL_UNITS = 130;
constexpr int UA = UNITS - TAIL_UNITS;
constexpr int TICKETS = UA + 2 * TAIL_UNITS;
constexpr int F_ROWS = 512;
constexpr int P_ROWS = 64;
constexpr int NP = F_ROWS / P_ROWS;
constexpr int F0 = UA * T - F_ROWS;
constexpr int QUARTERS = 4;
constexpr int QC = D / QUARTERS;
constexpr int CPT = G * QUARTERS;
constexpr int GW = 4;
constexpr int SG = 2 * GW;
constexpr int NSL = CPT / SG;
constexpr int RSLOTS = 16;
constexpr int RSTRIDE = 52;
constexpr int SLOT_WORDS = QUARTERS * 64;

constexpr int MBOX_STRIDE = 32;
constexpr int PACE_BASE = 285;
constexpr int PACE_DIV = 20700;

constexpr int W_FIN = 1;
constexpr int W_GATHER = 2;
constexpr int W_CONS = W_GATHER + GW;
constexpr int THREADS = (W_CONS + G) * 32;

constexpr int KV_BYTES = G * T * D * 4;
constexpr int ROWS_BYTES = T * D * 4;
constexpr int CS_BYTES = T * D * 2;
constexpr int SC_BYTES = G * 8 * 2;
constexpr int OFF_K = 0;
constexpr int OFF_V = KV_BYTES;
constexpr int OFF_COS = 2 * KV_BYTES;
constexpr int OFF_SIN = OFF_COS + CS_BYTES;
constexpr int OFF_KS = OFF_SIN + CS_BYTES;
constexpr int OFF_KZ = OFF_KS + SC_BYTES;
constexpr int OFF_VS = OFF_KZ + SC_BYTES;
constexpr int OFF_VZ = OFF_VS + SC_BYTES;
constexpr int STAGE_BYTES = OFF_VZ + SC_BYTES;
constexpr int KSIDE_BYTES = STAGE_BYTES - KV_BYTES;
constexpr int PIECE_BYTES = P_ROWS * QC * 4;

constexpr int BAR_FULLK = 0;
constexpr int BAR_FULLV = 8 * STAGES;
constexpr int BAR_EMPTY = 16 * STAGES;
constexpr int BAR_INIT = 24 * STAGES;
constexpr int BAR_END = BAR_INIT + 8;
constexpr int BAR_W = BAR_END + 8;
constexpr int BAR_G = BAR_W + 8;
constexpr int BAR_FIN = BAR_G + 8;
constexpr int OFF_UIDX = 224;
constexpr int OFF_TAG = OFF_UIDX + 4 * STAGES;
constexpr int OFF_TICKET = OFF_TAG + 4;
constexpr int LAST_BIT = 1 << 30;
constexpr int TAG_SHIFT = 29;
constexpr int POS_MASK = (1 << TAG_SHIFT) - 1;
constexpr int CTRL_BYTES = 256;
constexpr int OFF_W = CTRL_BYTES + STAGES * STAGE_BYTES;
constexpr int OFF_RV = OFF_W + F_ROWS * 4;
constexpr int OFF_RG = OFF_RV + RSLOTS * RSTRIDE * 4;
constexpr int SMEM_USED = OFF_W + 2 * KV_BYTES;
static_assert(OFF_RG + SG * RSTRIDE * 4 <= OFF_W + KV_BYTES / 2 && NP <= 2 * STAGES + 2, "final-phase buffers");
static_assert(BAR_FIN + 8 * NP <= OFF_UIDX && OFF_TICKET % 8 == 0, "control block");
constexpr int SMEM_BYTES = SMEM_USED;
static_assert(STAGE_BYTES % 128 == 0 && PIECE_BYTES % 128 == 0 && TEAMS == T, "layout");
static_assert(SMEM_BYTES <= 232448, "shared memory budget");

struct __align__(128) Scratch {
    float part[H * CPT * SLOT_WORDS];
    uint2 logit[H * F_ROWS];
    unsigned int mbox[H * QUARTERS * MBOX_STRIDE];
    unsigned long long ctr[16];
};
__device__ Scratch g_scratch;

__device__ __forceinline__ uint32_t smem_u32(const void* p) {
    return (uint32_t)__cvta_generic_to_shared(p);
}
__device__ __forceinline__ void mbar_init(uint32_t bar, int cnt) {
    asm volatile("mbarrier.init.shared::cta.b64 [%0], %1;" ::"r"(bar), "r"(cnt) : "memory");
}
__device__ __forceinline__ void mbar_expect_tx(uint32_t bar, uint32_t bytes) {
    asm volatile("mbarrier.arrive.expect_tx.shared::cta.b64 _, [%0], %1;" ::"r"(bar), "r"(bytes) : "memory");
}
__device__ __forceinline__ void mbar_arrive(uint32_t bar) {
    asm volatile("mbarrier.arrive.shared::cta.b64 _, [%0];" ::"r"(bar) : "memory");
}
__device__ __forceinline__ void mbar_wait(uint32_t bar, uint32_t parity) {
    asm volatile(
        "{\n"
        ".reg .pred p;\n"
        ".reg .u32 n;\n"
        "mov.u32 n, 0;\n"
        "WAIT_%=:\n"
        "add.u32 n, n, 1;\n"
        "mbarrier.try_wait.parity.shared::cta.b64 p, [%0], %1;\n"
        "setp.gt.or.u32 p, n, " "0x400000" ", p;\n"
        "@!p bra WAIT_%=;\n"
        "}" ::"r"(bar), "r"(parity) : "memory");
}
__device__ __forceinline__ bool mbar_test(uint32_t bar, uint32_t parity) {
    uint32_t ok;
    asm volatile("{\n.reg .pred p;\nmbarrier.test_wait.parity.shared::cta.b64 p, [%1], %2;\nselp.u32 %0, 1, 0, p;\n}"
                 : "=r"(ok) : "r"(bar), "r"(parity) : "memory");
    return ok != 0;
}
__device__ __forceinline__ uint32_t now_ns() {
    uint32_t t;
    asm volatile("mov.u32 %0, %%globaltimer_lo;" : "=r"(t)::"memory");
    return t;
}
__device__ __forceinline__ bool elect_one() {
    uint32_t p;
    asm volatile("{\n.reg .pred p;\nelect.sync _|p, 0xffffffff;\nselp.u32 %0, 1, 0, p;\n}" : "=r"(p));
    return p != 0;
}
__device__ __forceinline__ void bulk_load(uint32_t dst, const void* src, uint32_t bytes, uint32_t bar) {
    asm volatile("cp.async.bulk.shared::cluster.global.mbarrier::complete_tx::bytes [%0], [%1], %2, [%3];"
                 ::"r"(dst), "l"(src), "r"(bytes), "r"(bar) : "memory");
}
__device__ __forceinline__ void tma3d(uint32_t dst, const CUtensorMap* map, int c0, int c1, int c2,
                                      uint32_t bar, uint64_t pol) {
    asm volatile(
        "cp.async.bulk.tensor.3d.shared::cluster.global.mbarrier::complete_tx::bytes.L2::cache_hint"
        " [%0], [%1, {%2, %3, %4}], [%5], %6;"
        ::"r"(dst), "l"(map), "r"(c0), "r"(c1), "r"(c2), "r"(bar), "l"(pol) : "memory");
}
__device__ __forceinline__ void tma2d(uint32_t dst, const CUtensorMap* map, int c0, int c1, uint32_t bar) {
    asm volatile(
        "cp.async.bulk.tensor.2d.shared::cluster.global.mbarrier::complete_tx::bytes"
        " [%0], [%1, {%2, %3}], [%4];"
        ::"r"(dst), "l"(map), "r"(c0), "r"(c1), "r"(bar) : "memory");
}
__device__ __forceinline__ void prefetch_map(const CUtensorMap* map) {
    asm volatile("prefetch.tensormap [%0];" ::"l"(map) : "memory");
}
__device__ __forceinline__ uint64_t evict_first_policy() {
    uint64_t pol;
    asm volatile("createpolicy.fractional.L2::evict_first.b64 %0, 1.0;" : "=l"(pol));
    return pol;
}
__device__ __forceinline__ float ex2(float x) {
    float y;
    asm("ex2.approx.ftz.f32 %0, %1;" : "=f"(y) : "f"(x));
    return y;
}
__device__ __forceinline__ float bf_lo(uint32_t x) { return __uint_as_float(x << 16); }
__device__ __forceinline__ float bf_hi(uint32_t x) { return __uint_as_float(x & 0xffff0000u); }
__device__ __forceinline__ uint32_t bf2_mul(uint32_t a, uint32_t b) {
    uint32_t d;
    asm("mul.rn.bf16x2 %0, %1, %2;" : "=r"(d) : "r"(a), "r"(b));
    return d;
}
__device__ __forceinline__ uint32_t bf2_add(uint32_t a, uint32_t b) {
    uint32_t d;
    asm("add.rn.bf16x2 %0, %1, %2;" : "=r"(d) : "r"(a), "r"(b));
    return d;
}
__device__ __forceinline__ uint32_t bf2_sub(uint32_t a, uint32_t b) {
    uint32_t d;
    asm("sub.rn.bf16x2 %0, %1, %2;" : "=r"(d) : "r"(a), "r"(b));
    return d;
}
__device__ __forceinline__ float lds_bf16(uint32_t addr) {
    unsigned short v;
    asm volatile("ld.shared.u16 %0, [%1];" : "=h"(v) : "r"(addr));
    return __uint_as_float(((uint32_t)v) << 16);
}
__device__ __forceinline__ int4 lds128(uint32_t addr) {
    int4 v;
    asm volatile("ld.shared.v4.s32 {%0,%1,%2,%3}, [%4];" : "=r"(v.x), "=r"(v.y), "=r"(v.z), "=r"(v.w) : "r"(addr));
    return v;
}
__device__ __forceinline__ uint2 lds64(uint32_t addr) {
    uint2 v;
    asm volatile("ld.shared.v2.u32 {%0,%1}, [%2];" : "=r"(v.x), "=r"(v.y) : "r"(addr));
    return v;
}
__device__ __forceinline__ float2 lds64f(uint32_t addr) {
    const uint2 v = lds64(addr);
    return make_float2(__uint_as_float(v.x), __uint_as_float(v.y));
}
__device__ __forceinline__ uint32_t lds32(uint32_t addr) {
    uint32_t v;
    asm volatile("ld.shared.u32 %0, [%1];" : "=r"(v) : "r"(addr) : "memory");
    return v;
}
__device__ __forceinline__ void sts32(uint32_t addr, uint32_t v) {
    asm volatile("st.shared.u32 [%0], %1;" ::"r"(addr), "r"(v) : "memory");
}
__device__ __forceinline__ void sts128f(uint32_t addr, float a, float b, float c, float d) {
    asm volatile("st.shared.v4.f32 [%0], {%1,%2,%3,%4};" ::"r"(addr), "f"(a), "f"(b), "f"(c), "f"(d) : "memory");
}
__device__ __forceinline__ float warp_max(float x) {
    int k = __float_as_int(x);
    k ^= (k >> 31) & 0x7fffffff;
    k = __reduce_max_sync(0xffffffffu, k);
    return __int_as_float(k ^ ((k >> 31) & 0x7fffffff));
}

__device__ __forceinline__ uint32_t tagged(float x, uint32_t tag) { return (__float_as_uint(x) & ~1u) | tag; }

__device__ __forceinline__ void st_relaxed_b64(const void* p, uint32_t lo, uint32_t hi) {
    asm volatile("{\n.reg .b64 v;\nmov.b64 v, {%1,%2};\nst.relaxed.gpu.global.b64 [%0], v;\n}"
                 ::"l"(p), "r"(lo), "r"(hi) : "memory");
}
template <int OFF>
__device__ __forceinline__ uint4 ld_relaxed_2xb64(const void* base) {
    uint4 v;
    asm volatile("{\n.reg .b64 a, b;\nld.relaxed.gpu.global.v2.b64 {a, b}, [%4+%5];\n"
                 "mov.b64 {%0,%1}, a;\nmov.b64 {%2,%3}, b;\n}"
                 : "=r"(v.x), "=r"(v.y), "=r"(v.z), "=r"(v.w) : "l"(base), "n"(OFF) : "memory");
    return v;
}
__device__ __forceinline__ void mbox_post(unsigned int* box, unsigned int bits) {
    asm volatile("red.relaxed.gpu.global.add.u32 [%0], %1;" ::"l"(box), "r"(bits) : "memory");
}
__device__ __forceinline__ unsigned int mbox_take(unsigned int* box) {
    unsigned int v;
    asm volatile("atom.relaxed.gpu.global.exch.b32 %0, [%1], 0;" : "=r"(v) : "l"(box) : "memory");
    return v;
}
template <int OFF>
__device__ __forceinline__ uint2 ldg64(const void* base) {
    uint2 v;
    asm volatile("ld.global.nc.v2.u32 {%0,%1}, [%2+%3];" : "=r"(v.x), "=r"(v.y) : "l"(base), "n"(OFF));
    return v;
}
template <int N, typename F>
__device__ __forceinline__ void static_for(F&& f) {
    if constexpr (N > 0) {
        static_for<N - 1>(f);
        f(std::integral_constant<int, N - 1>{});
    }
}
__device__ __forceinline__ unsigned long long draw(unsigned long long* ctr, unsigned long long inc) {
    unsigned long long v;
    asm volatile("atom.relaxed.gpu.global.add.u64 %0, [%1], %2;" : "=l"(v) : "l"(ctr), "l"(inc) : "memory");
    return v;
}

__device__ __forceinline__ uint32_t piece_off(int p) {
    return CTRL_BYTES + KV_BYTES / 2 + (p >> 1) * STAGE_BYTES + (p & 1) * KV_BYTES;
}
static_assert(PIECE_BYTES == KV_BYTES / 2 && OFF_K == 0 && OFF_V == KV_BYTES, "piece placement");

struct Params {
    const int* qk;
    const __nv_bfloat16* k_cos;
    const __nv_bfloat16* k_sin;
    Scratch* scratch;
    const __nv_bfloat16* q;
    const __nv_bfloat16* q_cos;
    const __nv_bfloat16* q_sin;
    __nv_bfloat16* out;
};
struct Maps {
    CUtensorMap k, v, ks, kz, vs, vz, kh, vh, vf;
};

__global__ void __launch_bounds__(THREADS, 1)
kv_decode_kernel(const __grid_constant__ Params prm, const __grid_constant__ Maps maps) {
    extern __shared__ __align__(1024) unsigned char smem[];
    const uint32_t sb = __shfl_sync(0xffffffffu, smem_u32(smem), 0);
    if (threadIdx.x < 32 && elect_one()) {
        mbar_init(sb + BAR_FULLK, 1);
        asm volatile("fence.mbarrier_init.release.cluster;" ::: "memory");
        const uint32_t row = (blockIdx.x % TEAMS) * (G * S - 1) + blockIdx.x;
        const char* src = reinterpret_cast<const char*>(prm.qk) + row * (size_t)(D * 4);
        uint32_t dst = sb + CTRL_BYTES;
#pragma unroll 1
        do {
            bulk_load(dst, src, ROWS_BYTES, sb + BAR_FULLK);
            dst += ROWS_BYTES;
            src += S * D * 4;
        } while (dst != sb + CTRL_BYTES + KV_BYTES);
#pragma unroll
        for (int i = 1; i < BAR_FIN / 8 + NP; i++) mbar_init(sb + 8 * i, (unsigned)(i - BAR_EMPTY / 8) < STAGES ? G : 1);
        asm volatile("fence.mbarrier_init.release.cluster;" ::: "memory");
    }
    uint32_t bid;
    asm volatile("mov.u32 %0, %%ctaid.x;" : "=r"(bid));
    const int team = bid % TEAMS;
    const int cin = bid / TEAMS;
    const int h0 = team * G;
    const uint32_t buf0 = sb + CTRL_BYTES;
    const int warp = __shfl_sync(0xffffffffu, threadIdx.x >> 5, 0);
    const int lane = threadIdx.x & 31;

    if (warp >= W_CONS) {
        const int cw = warp - W_CONS;
        const int h = h0 + cw;
        const int r = lane >> 3;
        const int j = lane & 7;

        float qa[3][4], qb[3][4];
        {
            const __nv_bfloat16* qp = prm.q + h * D + 4 * j;
            const __nv_bfloat16* cp = prm.q_cos + 4 * j;
            const __nv_bfloat16* sp = prm.q_sin + 4 * j;
            static_for<3>([&](auto ic) {
                constexpr int i = decltype(ic)::value;
                const uint2 x1 = ldg64<64 * i>(qp), x2 = ldg64<64 * i + 2 * HALF>(qp);
                const uint2 c1 = ldg64<64 * i>(cp), c2 = ldg64<64 * i + 2 * HALF>(cp);
                const uint2 s1 = ldg64<64 * i>(sp), s2 = ldg64<64 * i + 2 * HALF>(sp);
                const uint32_t a0 = bf2_sub(bf2_mul(x1.x, c1.x), bf2_mul(x2.x, s1.x));
                const uint32_t a1 = bf2_sub(bf2_mul(x1.y, c1.y), bf2_mul(x2.y, s1.y));
                const uint32_t b0 = bf2_add(bf2_mul(x2.x, c2.x), bf2_mul(x1.x, s2.x));
                const uint32_t b1 = bf2_add(bf2_mul(x2.y, c2.y), bf2_mul(x1.y, s2.y));
                qa[i][0] = bf_lo(a0); qa[i][1] = bf_hi(a0); qa[i][2] = bf_lo(a1); qa[i][3] = bf_hi(a1);
                qb[i][0] = bf_lo(b0); qb[i][1] = bf_hi(b0); qb[i][2] = bf_lo(b1); qb[i][3] = bf_hi(b1);
            });
        }
        float acc[6][4];
#pragma unroll
        for (int i = 0; i < 6; i++)
#pragma unroll
            for (int c = 0; c < 4; c++) acc[i][c] = 0.f;
        float m_run = -3e38f, l_run = 0.f;
        float z_run = 0.f;

        const uint32_t va_off = OFF_V + ((lane & 16) ? 384 : 0);
        const uint32_t vb_off = OFF_V + ((lane & 16) ? 0 : 384);
        uint32_t kv_off = (uint32_t)((cw * T + r) * (D * 4) + j * 16);
        uint32_t cs_off = (uint32_t)(OFF_COS + r * (D * 2) + j * 8);
        uint32_t sc_off = (uint32_t)(OFF_KS + cw * 16 + r * 2);
        float mask = 0.f;

        asm volatile("bar.sync 0, %0;" ::"n"(THREADS) : "memory");

        int s = 0, word;
        uint32_t ph = 0;
#pragma unroll 1
        do {
            mbar_wait(sb + BAR_FULLK + 8 * s, ph);
            word = (int)lds32(sb + OFF_UIDX + 4 * s);
            const int pos = word & POS_MASK;
            if (pos >= UA * T) {
                kv_off = (uint32_t)((cw * (T / 2) + (r & 1)) * (D * 4) + j * 16);
                cs_off = (uint32_t)(OFF_COS + (r & 1) * (D * 2) + j * 8);
                sc_off = (uint32_t)(OFF_KS + cw * 16 + (r & 1) * 2);
                mask = r >= 2 ? -INFINITY : 0.f;
            }
            const uint32_t st = buf0 + s * STAGE_BYTES;
            const uint32_t sc = st + sc_off + (pos & 7) * 2;
            const float kz = lds_bf16(sc + SC_BYTES);
            const float ks = lds_bf16(sc) * QK_SCALE;
            const float vs = lds_bf16(sc + 2 * SC_BYTES);
            const float vz = lds_bf16(sc + 3 * SC_BYTES);

            float d0 = 0.f, d1 = 0.f;
#pragma unroll
            for (int i = 0; i < 3; i++) {
                const int4 ka = lds128(st + kv_off + i * 128);
                const int4 kb = lds128(st + kv_off + (i + 3) * 128);
                const uint2 ca = lds64(st + cs_off + i * 64);
                const uint2 cb = lds64(st + cs_off + (i + 3) * 64);
                const uint2 sa = lds64(st + cs_off + CS_BYTES + i * 64);
                const uint2 sb2 = lds64(st + cs_off + CS_BYTES + (i + 3) * 64);
                const float a[4] = {(float)ka.x - kz, (float)ka.y - kz, (float)ka.z - kz, (float)ka.w - kz};
                const float b[4] = {(float)kb.x - kz, (float)kb.y - kz, (float)kb.z - kz, (float)kb.w - kz};
                const float fca[4] = {bf_lo(ca.x), bf_hi(ca.x), bf_lo(ca.y), bf_hi(ca.y)};
                const float fcb[4] = {bf_lo(cb.x), bf_hi(cb.x), bf_lo(cb.y), bf_hi(cb.y)};
                const float fsa[4] = {bf_lo(sa.x), bf_hi(sa.x), bf_lo(sa.y), bf_hi(sa.y)};
                const float fsb[4] = {bf_lo(sb2.x), bf_hi(sb2.x), bf_lo(sb2.y), bf_hi(sb2.y)};
#pragma unroll
                for (int c = 0; c < 4; c++) {
                    const float ra = fmaf(a[c], fca[c], -b[c] * fsa[c]);
                    const float rb = fmaf(b[c], fcb[c], a[c] * fsb[c]);
                    d0 = fmaf(qa[i][c], ra, d0);
                    d1 = fmaf(qb[i][c], rb, d1);
                }
            }
            float dot = d0 + d1;
            dot += __shfl_xor_sync(0xffffffffu, dot, 1);
            dot += __shfl_xor_sync(0xffffffffu, dot, 2);
            dot += __shfl_xor_sync(0xffffffffu, dot, 4);
            const float sv = dot * ks;

            if ((unsigned)(pos - F0) < (unsigned)F_ROWS) {
                if (j == 0)
                    st_relaxed_b64(prm.scratch->logit + h * F_ROWS + (pos - F0) + r,
                                   (__float_as_uint(vs) >> 16) | __float_as_uint(vz),
                                   tagged(fmaxf(sv, -3e38f), (word >> TAG_SHIFT) & 1));
            } else {
                if (__any_sync(0xffffffffu, sv > m_run)) {
                    float m_new = fmaxf(sv, __shfl_xor_sync(0xffffffffu, sv, 8));
                    m_new = fmaxf(m_run, fmaxf(m_new, __shfl_xor_sync(0xffffffffu, m_new, 16)));
                    const float alpha = ex2(m_run - m_new);
                    l_run *= alpha;
                    z_run *= alpha;
#pragma unroll
                    for (int i = 0; i < 6; i++)
#pragma unroll
                        for (int c = 0; c < 4; c++) acc[i][c] *= alpha;
                    m_run = m_new;
                }
                const float p = ex2(sv - m_run + mask);
                const float pv = p * vs;
                l_run += p;
                z_run = fmaf(pv, vz, z_run);
                mbar_wait(sb + BAR_FULLV + 8 * s, ph);
#pragma unroll
                for (int i = 0; i < 6; i++) {
                    const int4 v = lds128(st + kv_off + (i < 3 ? va_off : vb_off) + (i % 3) * 128);
                    acc[i][0] = fmaf(pv, (float)v.x, acc[i][0]);
                    acc[i][1] = fmaf(pv, (float)v.y, acc[i][1]);
                    acc[i][2] = fmaf(pv, (float)v.z, acc[i][2]);
                    acc[i][3] = fmaf(pv, (float)v.w, acc[i][3]);
                }
            }
            __syncwarp();
            if (lane == 0) mbar_arrive(sb + BAR_EMPTY + 8 * s);
            if (++s == STAGES) { s = 0; ph ^= 1; }
        } while (!(word & LAST_BIT));

        {
            const uint32_t tag = (word >> TAG_SHIFT) & 1;
            char* slot = reinterpret_cast<char*>(prm.scratch->part + (h * CPT + cin) * SLOT_WORDS);
            char* part_st = slot + (lane & 16) * 32 + j * 16 + (lane & 8);
            l_run += __shfl_xor_sync(0xffffffffu, l_run, 8);
            z_run += __shfl_xor_sync(0xffffffffu, z_run, 8);
            l_run += __shfl_xor_sync(0xffffffffu, l_run, 16);
            z_run += __shfl_xor_sync(0xffffffffu, z_run, 16);
            st_relaxed_b64(slot + r * 256 + QC * 4 + j * 8, __float_as_uint(m_run), tagged(l_run, tag));
            const bool od = (lane & 8) != 0;
#pragma unroll
            for (int i = 0; i < 3; i++) {
                float k[4];
#pragma unroll
                for (int c = 0; c < 4; c++) k[c] = acc[i][c] + __shfl_xor_sync(0xffffffffu, acc[i + 3][c], 16);
                const float z0 = (od ? k[2] : k[0]) + __shfl_xor_sync(0xffffffffu, od ? k[0] : k[2], 8);
                const float z1 = (od ? k[3] : k[1]) + __shfl_xor_sync(0xffffffffu, od ? k[1] : k[3], 8);
                st_relaxed_b64(part_st + i * 128 + (i == 2 ? 64 : i == 1 ? (j & 4) * 16 : 0),
                               __float_as_uint(z0 - z_run), tagged(z1 - z_run, tag));
            }
            if (lane < QUARTERS) mbox_post(prm.scratch->mbox + (h * QUARTERS + lane) * MBOX_STRIDE, 1u);
        }

        if (cw >= RSLOTS * 12 / 32) return;
        const int ft = threadIdx.x - W_CONS * 32;
        const int rs = ft / 12;
        float a0 = 0.f, a1 = 0.f, a2 = 0.f, a3 = 0.f;
        mbar_wait(sb + BAR_W, 0);
        const uint32_t ra = sb + OFF_RV + rs * (RSTRIDE * 4 - QC * 4) + ft * 16;
#pragma unroll 1
        for (int p = 0; p < NP; p++) {
            const int4 w4 = lds128(sb + OFF_W + p * (P_ROWS * 4) + rs * 16);
            const float w[4] = {__int_as_float(w4.x), __int_as_float(w4.y), __int_as_float(w4.z), __int_as_float(w4.w)};
            const uint32_t va = sb + piece_off(p) + ft * 16;
            mbar_wait(sb + BAR_FIN + 8 * p, 0);
#pragma unroll
            for (int i = 0; i < 4; i++) {
                const int4 v = lds128(va + i * (RSLOTS * QC * 4));
                a0 = fmaf(w[i], (float)v.x, a0);
                a1 = fmaf(w[i], (float)v.y, a1);
                a2 = fmaf(w[i], (float)v.z, a2);
                a3 = fmaf(w[i], (float)v.w, a3);
            }
        }
        sts128f(ra, a0, a1, a2, a3);
        asm volatile("bar.arrive 3, %0;" ::"n"(RSLOTS * 12 + 32) : "memory");
        return;
    }

    if (warp >= W_GATHER) {
        asm volatile("bar.sync 0, %0;" ::"n"(THREADS) : "memory");
        const int sub = lane >= 13, quad = min(lane - sub * 13, 12);
        const int sg = 2 * (warp - W_GATHER) + sub;
        const float* src = prm.scratch->part + ((h0 + cin / QUARTERS) * CPT + sg) * SLOT_WORDS +
                           (cin % QUARTERS) * 64 + quad * 4;
        uint4 dt[NSL];
        mbar_wait(sb + BAR_INIT, 0);
        const uint32_t tag = lds32(sb + OFF_TAG);
        mbar_wait(sb + BAR_G, 0);
        int spin = 0;
        uint32_t bad;
#pragma unroll 1
        do {
            static_for<NSL>([&](auto bc) {
                constexpr int b = decltype(bc)::value;
                dt[b] = ld_relaxed_2xb64<b * SG * SLOT_WORDS * 4>(src);
            });
            bad = 0;
#pragma unroll
            for (int b = 0; b < NSL; b++) bad |= (dt[b].y ^ tag) | (dt[b].w ^ tag);
        } while (__any_sync(0xffffffffu, bad & 1u) && ++spin < (1 << 20));
        float mh[NSL], m = -INFINITY;
#pragma unroll
        for (int b = 0; b < NSL; b++) {
            mh[b] = __shfl_sync(0xffffffffu, __uint_as_float(dt[b].x), sub * 13 + 12);
            m = fmaxf(m, mh[b]);
        }
        float a0 = 0.f, a1 = 0.f, a2 = 0.f, a3 = 0.f;
#pragma unroll
        for (int b = 0; b < NSL; b++) {
            const float w = ex2(mh[b] - m);
            a0 = fmaf(w, __uint_as_float(dt[b].x), a0);
            a1 = fmaf(w, __uint_as_float(dt[b].y), a1);
            a2 = fmaf(w, __uint_as_float(dt[b].z), a2);
            a3 = fmaf(w, __uint_as_float(dt[b].w), a3);
        }
        if (lane < 26) sts128f(sb + OFF_RG + sg * (RSTRIDE * 4) + quad * 16, quad == 12 ? m : a0, a1, a2, a3);
        asm volatile("bar.arrive 2, %0;" ::"n"(GW * 32 + 32) : "memory");
        return;
    }

    if (warp == W_FIN) {
        if (elect_one()) {
            prefetch_map(&maps.ks);
            prefetch_map(&maps.kz);
            prefetch_map(&maps.vs);
            prefetch_map(&maps.vz);
            prefetch_map(&maps.k);
            prefetch_map(&maps.v);
        }
        asm volatile("bar.sync 0, %0;" ::"n"(THREADS) : "memory");
        const char* lptr = reinterpret_cast<const char*>(prm.scratch->logit + (h0 + cin / QUARTERS) * F_ROWS) + lane * 16;
        __nv_bfloat16* optr = prm.out + h0 * D + cin * QC + 2 * lane;
        mbar_wait(sb + BAR_INIT, 0);
        const uint32_t tag = lds32(sb + OFF_TAG);
        uint4 rec[NP];
        bool ok;
        int spin = 0;
        do {
            static_for<NP>([&](auto ic) { rec[decltype(ic)::value] = ld_relaxed_2xb64<decltype(ic)::value * 512>(lptr); });
            uint32_t bad = 0;
#pragma unroll
            for (int i = 0; i < NP; i++) bad |= (rec[i].y ^ tag) | (rec[i].w ^ tag);
            ok = (bad & 1u) == 0;
        } while (!__all_sync(0xffffffffu, ok) && ++spin < (1 << 20));
        float mF = -INFINITY, lF = 0.f, zF = 0.f;
#pragma unroll
        for (int i = 0; i < NP; i++) mF = fmaxf(mF, fmaxf(__uint_as_float(rec[i].y), __uint_as_float(rec[i].w)));
        mF = warp_max(mF);
        const uint32_t wa = sb + OFF_W + (lane & 7) * 32 + (lane >> 3) * 4;
#pragma unroll
        for (int i = 0; i < NP; i++) {
            const float p0 = ex2(__uint_as_float(rec[i].y) - mF), p1 = ex2(__uint_as_float(rec[i].w) - mF);
            const float a0 = p0 * bf_lo(rec[i].x), a1 = p1 * bf_lo(rec[i].z);
            lF += p0 + p1;
            zF = fmaf(a0, bf_hi(rec[i].x), fmaf(a1, bf_hi(rec[i].z), zF));
            sts32(wa + i * (P_ROWS * 4), __float_as_uint(a0));
            sts32(wa + i * (P_ROWS * 4) + 16, __float_as_uint(a1));
        }
        __syncwarp();
        if (lane == 0) mbar_arrive(sb + BAR_W);
#pragma unroll
        for (int o = 16; o > 0; o >>= 1) {
            lF += __shfl_xor_sync(0xffffffffu, lF, o);
            zF += __shfl_xor_sync(0xffffffffu, zF, o);
        }
        mbar_wait(sb + BAR_END, 0);
        if (lane == 0) {
            unsigned int* box = prm.scratch->mbox + (h0 * QUARTERS + cin) * MBOX_STRIDE;
            int seen = 0;
            do seen += mbox_take(box); while (seen < CPT && ++spin < (1 << 20));
            mbar_arrive(sb + BAR_G);
        }
        __syncwarp();
        const uint32_t col = sb + (uint32_t)min(lane, QC / 2 - 1) * 8;
        asm volatile("bar.sync 2, %0;" ::"r"(__float_as_uint(lF + zF) == 0xffffffffu ? 32 : GW * 32 + 32) : "memory");
        float2 ml[SG], ga[SG];
#pragma unroll
        for (int g = 0; g < SG; g++) {
            ml[g] = lds64f(sb + OFF_RG + g * (RSTRIDE * 4) + QC * 4);
            ga[g] = lds64f(col + OFF_RG + g * (RSTRIDE * 4));
        }
        float M = mF;
#pragma unroll
        for (int g = 0; g < SG; g++) M = fmaxf(M, ml[g].x);
        float wF = ex2(mF - M);
        float L = wF * lF, b0 = -wF * zF, b1 = b0;
#pragma unroll
        for (int g = 0; g < SG; g++) {
            const float w = ex2(ml[g].x - M);
            L = fmaf(w, ml[g].y, L);
            b0 = fmaf(w, ga[g].x, b0);
            b1 = fmaf(w, ga[g].y, b1);
        }
        const float inv = __fdividef(1.f, L);
        wF *= inv;
        b0 *= inv;
        b1 *= inv;
        asm volatile("bar.sync 3, %0;"
                     ::"r"(__any_sync(0xffffffffu, __float_as_uint(wF + b0 + b1) == 0xffffffffu) ? 32 : RSLOTS * 12 + 32) : "memory");
        float2 rv[RSLOTS];
#pragma unroll
        for (int g = 0; g < RSLOTS; g++) rv[g] = lds64f(col + OFF_RV + g * (RSTRIDE * 4));
        static_for<4>([&](auto lc) {
            constexpr int o = RSLOTS / 2 >> decltype(lc)::value;
#pragma unroll
            for (int g = 0; g < o; g++) {
                rv[g].x += rv[g + o].x;
                rv[g].y += rv[g + o].y;
            }
        });
        if (lane < QC / 2)
            *reinterpret_cast<__nv_bfloat162*>(optr) = __floats2bfloat162_rn(fmaf(wF, rv[0].x, b0), fmaf(wF, rv[0].y, b1));
        return;
    }

    __syncwarp();
    asm volatile("bar.arrive 0, %0;" ::"n"(THREADS) : "memory");
    if (!elect_one()) return;
    const uint64_t pol = evict_first_policy();
    unsigned long long* ctr = prm.scratch->ctr;
    constexpr int total = TICKETS - (STAGES - 1) * CPT;
    const unsigned long long inc = 1ull << (15 * team);
    unsigned long long ticket = draw(ctr, inc);
    const uint32_t t_begin = now_ns();
    uint32_t w1 = 0, w2 = 0, w3 = 0;
    auto push = [&](uint32_t w) { w3 = w2; w2 = w1; w1 = w; };
    int s = 0, u = cin, k = 0, halves = 0, drawn = 0;
    uint32_t ph = 0;
    uint32_t t_draw = 0;
    bool init_done = false;
#pragma unroll 1
    for (;; k++) {
        const bool half = u >= UA;
        const int pos = half ? (u + UA) * (T / 2) : u * T;
        const int p8 = pos & ~7;
        const uint32_t fb = sb + BAR_FULLK + 8 * s;
        const uint32_t fv = sb + BAR_FULLV + 8 * s;
        const uint32_t dst = buf0 + s * STAGE_BYTES;
        halves += half;
        const bool gated = k >= STAGES && halves < STAGES;
        mbar_wait(sb + BAR_EMPTY + 8 * s, ph ^ 1);
        if (gated) mbar_wait(w3 & ~1u, w3 & 1u);
        if (k > 0) tma3d(dst + OFF_K, half ? &maps.kh : &maps.k, 0, pos, h0, fb, pol);
        bulk_load(dst + OFF_COS, prm.k_cos + (size_t)pos * D, half ? CS_BYTES / 2 : CS_BYTES, fb);
        bulk_load(dst + OFF_SIN, prm.k_sin + (size_t)pos * D, half ? CS_BYTES / 2 : CS_BYTES, fb);
        tma2d(dst + OFF_KS, &maps.ks, p8, h0, fb);
        tma2d(dst + OFF_KZ, &maps.kz, p8, h0, fb);
        tma2d(dst + OFF_VS, &maps.vs, p8, h0, fb);
        tma2d(dst + OFF_VZ, &maps.vz, p8, h0, fb);
        if (k >= STAGES) ticket = draw(ctr, inc);
        if (half) t_draw = now_ns();
        push(fb | ph);
        if ((unsigned)(pos - F0) < (unsigned)F_ROWS) {
            mbar_arrive(fv);
            prefetch_map(&maps.kh);
            prefetch_map(&maps.vh);
            prefetch_map(&maps.vf);
        } else {
            if (gated) mbar_wait(w3 & ~1u, w3 & 1u);
            mbar_expect_tx(fv, half ? KV_BYTES / 2 : KV_BYTES);
            tma3d(dst + OFF_V, half ? &maps.vh : &maps.v, 0, pos, h0, fv, pol);
            push(fv | ph);
        }
        int un = u + CPT;
        uint32_t tag = 0;
        if (k >= STAGES - 1) {
            uint32_t lo, hi;
            asm volatile("st.shared.b64 [%2], %3;\nld.volatile.shared.v2.u32 {%0,%1}, [%2];"
                         : "=r"(lo), "=r"(hi) : "r"(sb + OFF_TICKET), "l"(ticket) : "memory");
            const int t01 = (int)(lo & 0x3fffffff), t23 = (int)(__funnelshift_r(lo, hi, 30) & 0x3fffffff);
            const int t = ((team & 2 ? t23 : t01) >> (15 * (team & 1))) & 0x7fff;
            drawn = (t01 & 0x7fff) + (t01 >> 15) + (t23 & 0x7fff) + (t23 >> 15);
            tag = ~hi >> 31;
            un = STAGES * CPT + t;
        }
        const bool start_fin = !init_done && un >= TICKETS - 2 * CPT;
        init_done |= start_fin;
        sts32(sb + OFF_UIDX + 4 * s, pos | (tag << TAG_SHIFT) | (un >= TICKETS ? LAST_BIT : 0));
        mbar_expect_tx(fb, half ? KSIDE_BYTES - KV_BYTES / 2 - CS_BYTES : KSIDE_BYTES);
        if (start_fin) {
            sts32(sb + OFF_TAG, tag);
            mbar_arrive(sb + BAR_INIT);
        }
        if (un >= TICKETS) break;
        u = un;
        if (++s == STAGES) { s = 0; ph ^= 1; }
    }
    mbar_arrive(sb + BAR_END);
    if (drawn == TEAMS * total - 1) draw(ctr, (1ull << 63) - total * 0x0000200040008001ull);
    uint32_t t_next = now_ns();
    int dt = (int)(t_draw - t_next) +
             (int)(((t_draw - t_begin) >> 4) * (uint32_t)(PACE_BASE + min(TEAMS * total - drawn, 512)) / (PACE_DIV / 16));
    dt = max(dt, 0) / NP;
    if (halves < STAGES) {
        mbar_wait(sb + BAR_EMPTY + 8 * s, ph);
        dt = 0;
    }
#pragma unroll 1
    for (int p = 0; p < NP; p++) {
        const uint32_t fb = sb + BAR_FIN + 8 * p;
        t_next += dt;
        while ((int)(now_ns() - t_next) < 0 && !mbar_test(w2 & ~1u, w2 & 1u)) {}
        mbar_expect_tx(fb, PIECE_BYTES);
        tma3d(sb + piece_off(p), &maps.vf, (cin % QUARTERS) * QC, F0 + p * P_ROWS, h0 + cin / QUARTERS, fb, pol);
        push(fb);
    }
}

__global__ void __launch_bounds__(128)
fallback_partial_kernel(const Params prm, const int* qv, const __nv_bfloat16* ks, const __nv_bfloat16* kz,
                        const __nv_bfloat16* vs, const __nv_bfloat16* vz) {
    const int h = blockIdx.y, slot = blockIdx.x * 4 + (threadIdx.x >> 5), lane = threadIdx.x & 31;
    float qa[3], qb[3], acc[6] = {0.f, 0.f, 0.f, 0.f, 0.f, 0.f};
    for (int i = 0; i < 3; i++) {
        const int d = 32 * i + lane;
        const __nv_bfloat16 x1 = prm.q[h * D + d], x2 = prm.q[h * D + d + HALF];
        qa[i] = __bfloat162float(__hsub_rn(__hmul_rn(x1, prm.q_cos[d]), __hmul_rn(x2, prm.q_sin[d])));
        qb[i] = __bfloat162float(__hadd_rn(__hmul_rn(x2, prm.q_cos[d + HALF]), __hmul_rn(x1, prm.q_sin[d + HALF])));
    }
    float m = -3e38f, l = 0.f;
    for (int pos = slot; pos < S; pos += CPT) {
        const size_t row = (size_t)h * S + pos;
        const float z = __bfloat162float(kz[row]);
        float dot = 0.f;
        for (int i = 0; i < 3; i++) {
            const int d = 32 * i + lane;
            const float a = (float)prm.qk[row * D + d] - z, b = (float)prm.qk[row * D + d + HALF] - z;
            const __nv_bfloat16* c = prm.k_cos + pos * D + d;
            const __nv_bfloat16* sn = prm.k_sin + pos * D + d;
            dot += qa[i] * (a * __bfloat162float(c[0]) - b * __bfloat162float(sn[0])) +
                   qb[i] * (b * __bfloat162float(c[HALF]) + a * __bfloat162float(sn[HALF]));
        }
        for (int o = 16; o > 0; o >>= 1) dot += __shfl_xor_sync(0xffffffffu, dot, o);
        const float sv = dot * __bfloat162float(ks[row]) * QK_SCALE;
        const float m_new = fmaxf(m, sv), alpha = ex2(m - m_new), p = ex2(sv - m_new);
        const float pv = p * __bfloat162float(vs[row]), zv = __bfloat162float(vz[row]);
        m = m_new;
        l = l * alpha + p;
        for (int i = 0; i < 6; i++) acc[i] = acc[i] * alpha + pv * ((float)qv[row * D + 32 * i + lane] - zv);
    }
    float* dst = prm.scratch->part + (h * CPT + slot) * SLOT_WORDS;
    for (int i = 0; i < 6; i++) dst[32 * i + lane] = acc[i];
    if (lane == 0) {
        dst[D] = m;
        dst[D + 1] = l;
    }
}

__global__ void __launch_bounds__(D) fallback_merge_kernel(const Params prm) {
    const float* src = prm.scratch->part + blockIdx.x * CPT * SLOT_WORDS;
    float m = -3e38f, l = 0.f, o = 0.f;
    for (int c = 0; c < CPT; c++) m = fmaxf(m, src[c * SLOT_WORDS + D]);
    for (int c = 0; c < CPT; c++) {
        const float w = ex2(src[c * SLOT_WORDS + D] - m);
        l += w * src[c * SLOT_WORDS + D + 1];
        o += w * src[c * SLOT_WORDS + threadIdx.x];
    }
    prm.out[blockIdx.x * D + threadIdx.x] = __float2bfloat16_rn(o / l);
}

typedef CUresult (*EncodeTiledFn)(CUtensorMap*, CUtensorMapDataType, cuuint32_t, void*, const cuuint64_t*,
                                  const cuuint64_t*, const cuuint32_t*, const cuuint32_t*,
                                  CUtensorMapInterleave, CUtensorMapSwizzle, CUtensorMapL2promotion,
                                  CUtensorMapFloatOOBfill);

void make_kv_map(EncodeTiledFn enc, CUtensorMap* m, const void* ptr, int cols, int rows, int heads,
                 CUtensorMapL2promotion promo) {
    cuuint64_t dims[3] = {(cuuint64_t)D, (cuuint64_t)S, (cuuint64_t)H};
    cuuint64_t strides[2] = {(cuuint64_t)D * 4, (cuuint64_t)S * D * 4};
    cuuint32_t box[3] = {(cuuint32_t)cols, (cuuint32_t)rows, (cuuint32_t)heads};
    cuuint32_t es[3] = {1, 1, 1};
    enc(m, CU_TENSOR_MAP_DATA_TYPE_INT32, 3, const_cast<void*>(ptr), dims, strides, box, es,
        CU_TENSOR_MAP_INTERLEAVE_NONE, CU_TENSOR_MAP_SWIZZLE_NONE, promo, CU_TENSOR_MAP_FLOAT_OOB_FILL_NONE);
}

void make_scale_map(EncodeTiledFn enc, CUtensorMap* m, const void* ptr) {
    cuuint64_t dims[2] = {(cuuint64_t)S, (cuuint64_t)H};
    cuuint64_t strides[1] = {(cuuint64_t)S * 2};
    cuuint32_t box[2] = {8, (cuuint32_t)G};
    cuuint32_t es[2] = {1, 1};
    enc(m, CU_TENSOR_MAP_DATA_TYPE_BFLOAT16, 2, const_cast<void*>(ptr), dims, strides, box, es,
        CU_TENSOR_MAP_INTERLEAVE_NONE, CU_TENSOR_MAP_SWIZZLE_NONE, CU_TENSOR_MAP_L2_PROMOTION_NONE,
        CU_TENSOR_MAP_FLOAT_OOB_FILL_NONE);
}

}

extern "C" void kernel_launch(void* const* d_in, const int* in_sizes, int n_in, void* d_out, int out_size) {
    (void)in_sizes; (void)n_in; (void)out_size;
    static EncodeTiledFn enc = nullptr;
    static Scratch* scratch = nullptr;
    static int sms = 0;
    if (!enc) {
        void* fn = nullptr;
        cudaDriverEntryPointQueryResult qr;
        cudaGetDriverEntryPoint("cuTensorMapEncodeTiled", &fn, cudaEnableDefault, &qr);
        enc = (EncodeTiledFn)fn;
        int dev = 0;
        cudaGetDevice(&dev);
        cudaDeviceGetAttribute(&sms, cudaDevAttrMultiProcessorCount, dev);
        cudaGetSymbolAddress((void**)&scratch, g_scratch);
        cudaFuncSetAttribute(kv_decode_kernel, cudaFuncAttributeMaxDynamicSharedMemorySize, SMEM_BYTES);
    }
    Params prm;
    prm.q = (const __nv_bfloat16*)d_in[0];
    prm.qk = (const int*)d_in[1];
    prm.q_cos = (const __nv_bfloat16*)d_in[7];
    prm.q_sin = (const __nv_bfloat16*)d_in[8];
    prm.k_cos = (const __nv_bfloat16*)d_in[9];
    prm.k_sin = (const __nv_bfloat16*)d_in[10];
    prm.out = (__nv_bfloat16*)d_out;
    prm.scratch = scratch;
    if (sms < TEAMS * CPT) {
        fallback_partial_kernel<<<dim3(CPT / 4, H), 128>>>(
            prm, (const int*)d_in[4], (const __nv_bfloat16*)d_in[2], (const __nv_bfloat16*)d_in[3],
            (const __nv_bfloat16*)d_in[5], (const __nv_bfloat16*)d_in[6]);
        fallback_merge_kernel<<<H, D>>>(prm);
        return;
    }
    Maps maps;
    make_kv_map(enc, &maps.k, prm.qk, D, T, G, CU_TENSOR_MAP_L2_PROMOTION_L2_128B);
    make_kv_map(enc, &maps.v, d_in[4], D, T, G, CU_TENSOR_MAP_L2_PROMOTION_L2_128B);
    make_kv_map(enc, &maps.kh, prm.qk, D, T / 2, G, CU_TENSOR_MAP_L2_PROMOTION_L2_128B);
    make_kv_map(enc, &maps.vh, d_in[4], D, T / 2, G, CU_TENSOR_MAP_L2_PROMOTION_L2_128B);
    make_kv_map(enc, &maps.vf, d_in[4], QC, P_ROWS, 1, CU_TENSOR_MAP_L2_PROMOTION_NONE);
    make_scale_map(enc, &maps.ks, d_in[2]);
    make_scale_map(enc, &maps.kz, d_in[3]);
    make_scale_map(enc, &maps.vs, d_in[5]);
    make_scale_map(enc, &maps.vz, d_in[6]);

    kv_decode_kernel<<<TEAMS * CPT, THREADS, SMEM_BYTES>>>(prm, maps);
}
```

```cpp
#include <cuda_runtime.h>
#include <cuda_bf16.h>
#include <cuda.h>
#include <stdint.h>
#include <type_traits>

namespace {

constexpr int H = 32;
constexpr int S = 16384;
constexpr int D = 192;
constexpr int HALF = D / 2;
constexpr float QK_SCALE = 0.07216878364870322f * 1.4426950408889634f;

constexpr int G = 8;
constexpr int T = 4;
constexpr int TEAMS = H / G;
constexpr int UNITS = S / T;
constexpr int STAGES = 3;
constexpr int TAIL_UNITS = 130;
constexpr int UA = UNITS - TAIL_UNITS;
constexpr int TICKETS = UA + 2 * TAIL_UNITS;
constexpr int F_ROWS = 512;
constexpr int P_ROWS = 64;
constexpr int NP = F_ROWS / P_ROWS;
constexpr int F0 = UA * T - F_ROWS;
constexpr int QUARTERS = 4;
constexpr int QC = D / QUARTERS;
constexpr int CPT = G * QUARTERS;
constexpr int GW = 4;
constexpr int SG = 2 * GW;
constexpr int NSL = CPT / SG;
constexpr int RSLOTS = 16;
constexpr int RSTRIDE = 52;
constexpr int SLOT_WORDS = QUARTERS * 64;

constexpr int MBOX_STRIDE = 32;
constexpr int PACE_BASE = 285;
constexpr int PACE_DIV = 20700;

constexpr int W_FIN = 1;
constexpr int W_GATHER = 2;
constexpr int W_CONS = W_GATHER + GW;
constexpr int THREADS = (W_CONS + G) * 32;

constexpr int KV_BYTES = G * T * D * 4;
constexpr int ROWS_BYTES = T * D * 4;
constexpr int CS_BYTES = T * D * 2;
constexpr int SC_BYTES = G * 8 * 2;
constexpr int OFF_K = 0;
constexpr int OFF_V = KV_BYTES;
constexpr int OFF_COS = 2 * KV_BYTES;
constexpr int OFF_SIN = OFF_COS + CS_BYTES;
constexpr int OFF_KS = OFF_SIN + CS_BYTES;
constexpr int OFF_KZ = OFF_KS + SC_BYTES;
constexpr int OFF_VS = OFF_KZ + SC_BYTES;
constexpr int OFF_VZ = OFF_VS + SC_BYTES;
constexpr int STAGE_BYTES = OFF_VZ + SC_BYTES;
constexpr int KSIDE_BYTES = STAGE_BYTES - KV_BYTES;
constexpr int PIECE_BYTES = P_ROWS * QC * 4;

constexpr int BAR_FULLK = 0;
constexpr int BAR_FULLV = 8 * STAGES;
constexpr int BAR_EMPTY = 16 * STAGES;
constexpr int BAR_INIT = 24 * STAGES;
constexpr int BAR_END = BAR_INIT + 8;
constexpr int BAR_W = BAR_END + 8;
constexpr int BAR_G = BAR_W + 8;
constexpr int BAR_FIN = BAR_G + 8;
constexpr int OFF_UIDX = 224;
constexpr int OFF_TAG = OFF_UIDX + 4 * STAGES;
constexpr int OFF_TICKET = OFF_TAG + 4;
constexpr int LAST_BIT = 1 << 30;
constexpr int TAG_SHIFT = 29;
constexpr int POS_MASK = (1 << TAG_SHIFT) - 1;
constexpr int CTRL_BYTES = 256;
constexpr int OFF_W = CTRL_BYTES + STAGES * STAGE_BYTES;
constexpr int OFF_RV = OFF_W + F_ROWS * 4;
constexpr int OFF_RG = OFF_RV + RSLOTS * RSTRIDE * 4;
constexpr int SMEM_USED = OFF_W + 2 * KV_BYTES;
static_assert(OFF_RG + SG * RSTRIDE * 4 <= OFF_W + KV_BYTES / 2 && NP <= 2 * STAGES + 2, "final-phase buffers");
static_assert(BAR_FIN + 8 * NP <= OFF_UIDX && OFF_TICKET % 8 == 0, "control block");
constexpr int SMEM_BYTES = SMEM_USED;
static_assert(STAGE_BYTES % 128 == 0 && PIECE_BYTES % 128 == 0 && TEAMS == T, "layout");
static_assert(SMEM_BYTES <= 232448, "shared memory budget");

struct __align__(128) Scratch {
    float part[H * CPT * SLOT_WORDS];
    uint2 logit[H * F_ROWS];
    unsigned int mbox[H * QUARTERS * MBOX_STRIDE];
    unsigned long long ctr[16];
};
__device__ Scratch g_scratch;

__device__ __forceinline__ uint32_t smem_u32(const void* p) {
    return (uint32_t)__cvta_generic_to_shared(p);
}
__device__ __forceinline__ void mbar_init(uint32_t bar, int cnt) {
    asm volatile("mbarrier.init.shared::cta.b64 [%0], %1;" ::"r"(bar), "r"(cnt) : "memory");
}
__device__ __forceinline__ void mbar_expect_tx(uint32_t bar, uint32_t bytes) {
    asm volatile("mbarrier.arrive.expect_tx.shared::cta.b64 _, [%0], %1;" ::"r"(bar), "r"(bytes) : "memory");
}
__device__ __forceinline__ void mbar_arrive(uint32_t bar) {
    asm volatile("mbarrier.arrive.shared::cta.b64 _, [%0];" ::"r"(bar) : "memory");
}
__device__ __forceinline__ void mbar_wait(uint32_t bar, uint32_t parity) {
    asm volatile(
        "{\n"
        ".reg .pred p;\n"
        ".reg .u32 n;\n"
        "mov.u32 n, 0;\n"
        "WAIT_%=:\n"
        "add.u32 n, n, 1;\n"
        "mbarrier.try_wait.parity.shared::cta.b64 p, [%0], %1;\n"
        "setp.gt.or.u32 p, n, " "0x400000" ", p;\n"
        "@!p bra WAIT_%=;\n"
        "}" ::"r"(bar), "r"(parity) : "memory");
}
__device__ __forceinline__ bool mbar_test(uint32_t bar, uint32_t parity) {
    uint32_t ok;
    asm volatile("{\n.reg .pred p;\nmbarrier.test_wait.parity.shared::cta.b64 p, [%1], %2;\nselp.u32 %0, 1, 0, p;\n}"
                 : "=r"(ok) : "r"(bar), "r"(parity) : "memory");
    return ok != 0;
}
__device__ __forceinline__ uint32_t now_ns() {
    uint32_t t;
    asm volatile("mov.u32 %0, %%globaltimer_lo;" : "=r"(t)::"memory");
    return t;
}
__device__ __forceinline__ bool elect_one() {
    uint32_t p;
    asm volatile("{\n.reg .pred p;\nelect.sync _|p, 0xffffffff;\nselp.u32 %0, 1, 0, p;\n}" : "=r"(p));
    return p != 0;
}
__device__ __forceinline__ void bulk_load(uint32_t dst, const void* src, uint32_t bytes, uint32_t bar) {
    asm volatile("cp.async.bulk.shared::cluster.global.mbarrier::complete_tx::bytes [%0], [%1], %2, [%3];"
                 ::"r"(dst), "l"(src), "r"(bytes), "r"(bar) : "memory");
}
__device__ __forceinline__ void tma3d(uint32_t dst, const CUtensorMap* map, int c0, int c1, int c2,
                                      uint32_t bar, uint64_t pol) {
    asm volatile(
        "cp.async.bulk.tensor.3d.shared::cluster.global.mbarrier::complete_tx::bytes.L2::cache_hint"
        " [%0], [%1, {%2, %3, %4}], [%5], %6;"
        ::"r"(dst), "l"(map), "r"(c0), "r"(c1), "r"(c2), "r"(bar), "l"(pol) : "memory");
}
__device__ __forceinline__ void tma2d(uint32_t dst, const CUtensorMap* map, int c0, int c1, uint32_t bar) {
    asm volatile(
        "cp.async.bulk.tensor.2d.shared::cluster.global.mbarrier::complete_tx::bytes"
        " [%0], [%1, {%2, %3}], [%4];"
        ::"r"(dst), "l"(map), "r"(c0), "r"(c1), "r"(bar) : "memory");
}
__device__ __forceinline__ void l2_prefetch(const void* src, uint32_t bytes) {
    asm volatile("cp.async.bulk.prefetch.L2.global [%0], %1;" ::"l"(src), "r"(bytes) : "memory");
}
__device__ __forceinline__ void prefetch_map(const CUtensorMap* map) {
    asm volatile("prefetch.tensormap [%0];" ::"l"(map) : "memory");
}
__device__ __forceinline__ uint64_t evict_first_policy() {
    uint64_t pol;
    asm volatile("createpolicy.fractional.L2::" "evict_first.b64 %0, 1.0" ";" : "=l"(pol));
    return pol;
}
__device__ __forceinline__ float ex2(float x) {
    float y;
    asm("ex2.approx.ftz.f32 %0, %1;" : "=f"(y) : "f"(x));
    return y;
}
__device__ __forceinline__ float bf_lo(uint32_t x) { return __uint_as_float(x << 16); }
__device__ __forceinline__ float bf_hi(uint32_t x) { return __uint_as_float(x & 0xffff0000u); }
__device__ __forceinline__ uint32_t bf2_mul(uint32_t a, uint32_t b) {
    uint32_t d;
    asm("mul.rn.bf16x2 %0, %1, %2;" : "=r"(d) : "r"(a), "r"(b));
    return d;
}
__device__ __forceinline__ uint32_t bf2_add(uint32_t a, uint32_t b) {
    uint32_t d;
    asm("add.rn.bf16x2 %0, %1, %2;" : "=r"(d) : "r"(a), "r"(b));
    return d;
}
__device__ __forceinline__ uint32_t bf2_sub(uint32_t a, uint32_t b) {
    uint32_t d;
    asm("sub.rn.bf16x2 %0, %1, %2;" : "=r"(d) : "r"(a), "r"(b));
    return d;
}
__device__ __forceinline__ float lds_bf16(uint32_t addr) {
    unsigned short v;
    asm volatile("ld.shared.u16 %0, [%1];" : "=h"(v) : "r"(addr));
    return __uint_as_float(((uint32_t)v) << 16);
}
__device__ __forceinline__ int4 lds128(uint32_t addr) {
    int4 v;
    asm volatile("ld.shared.v4.s32 {%0,%1,%2,%3}, [%4];" : "=r"(v.x), "=r"(v.y), "=r"(v.z), "=r"(v.w) : "r"(addr));
    return v;
}
__device__ __forceinline__ uint2 lds64(uint32_t addr) {
    uint2 v;
    asm volatile("ld.shared.v2.u32 {%0,%1}, [%2];" : "=r"(v.x), "=r"(v.y) : "r"(addr));
    return v;
}
__device__ __forceinline__ float2 lds64f(uint32_t addr) {
    const uint2 v = lds64(addr);
    return make_float2(__uint_as_float(v.x), __uint_as_float(v.y));
}
__device__ __forceinline__ uint32_t lds32(uint32_t addr) {
    uint32_t v;
    asm volatile("ld.shared.u32 %0, [%1];" : "=r"(v) : "r"(addr) : "memory");
    return v;
}
__device__ __forceinline__ void sts32(uint32_t addr, uint32_t v) {
    asm volatile("st.shared.u32 [%0], %1;" ::"r"(addr), "r"(v) : "memory");
}
__device__ __forceinline__ void sts128f(uint32_t addr, float a, float b, float c, float d) {
    asm volatile("st.shared.v4.f32 [%0], {%1,%2,%3,%4};" ::"r"(addr), "f"(a), "f"(b), "f"(c), "f"(d) : "memory");
}
__device__ __forceinline__ float warp_max(float x) {
    int k = __float_as_int(x);
    k ^= (k >> 31) & 0x7fffffff;
    k = __reduce_max_sync(0xffffffffu, k);
    return __int_as_float(k ^ ((k >> 31) & 0x7fffffff));
}

__device__ __forceinline__ uint32_t tagged(float x, uint32_t tag) { return (__float_as_uint(x) & ~1u) | tag; }

__device__ __forceinline__ void st_relaxed_b64(const void* p, uint32_t lo, uint32_t hi) {
    asm volatile("{\n.reg .b64 v;\nmov.b64 v, {%1,%2};\nst.relaxed.gpu.global.b64 [%0], v;\n}"
                 ::"l"(p), "r"(lo), "r"(hi) : "memory");
}
template <int OFF>
__device__ __forceinline__ uint4 ld_relaxed_2xb64(const void* base) {
    uint4 v;
    asm volatile("{\n.reg .b64 a, b;\nld.relaxed.gpu.global.v2.b64 {a, b}, [%4+%5];\n"
                 "mov.b64 {%0,%1}, a;\nmov.b64 {%2,%3}, b;\n}"
                 : "=r"(v.x), "=r"(v.y), "=r"(v.z), "=r"(v.w) : "l"(base), "n"(OFF) : "memory");
    return v;
}
__device__ __forceinline__ void mbox_post(unsigned int* box, unsigned int bits) {
    asm volatile("red.relaxed.gpu.global.add.u32 [%0], %1;" ::"l"(box), "r"(bits) : "memory");
}
__device__ __forceinline__ unsigned int mbox_take(unsigned int* box) {
    unsigned int v;
    asm volatile("atom.relaxed.gpu.global.exch.b32 %0, [%1], 0;" : "=r"(v) : "l"(box) : "memory");
    return v;
}
template <int OFF>
__device__ __forceinline__ uint2 ldg64(const void* base) {
    uint2 v;
    asm volatile("ld.global.nc.v2.u32 {%0,%1}, [%2+%3];" : "=r"(v.x), "=r"(v.y) : "l"(base), "n"(OFF));
    return v;
}
template <int N, typename F>
__device__ __forceinline__ void static_for(F&& f) {
    if constexpr (N > 0) {
        static_for<N - 1>(f);
        f(std::integral_constant<int, N - 1>{});
    }
}
__device__ __forceinline__ unsigned long long draw(unsigned long long* ctr, unsigned long long inc) {
    unsigned long long v;
    asm volatile("atom.relaxed.gpu.global.add.u64 %0, [%1], %2;" : "=l"(v) : "l"(ctr), "l"(inc) : "memory");
    return v;
}

__device__ __forceinline__ uint32_t piece_off(int p) {
    return CTRL_BYTES + KV_BYTES / 2 + (p >> 1) * STAGE_BYTES + (p & 1) * KV_BYTES;
}
static_assert(PIECE_BYTES == KV_BYTES / 2 && OFF_K == 0 && OFF_V == KV_BYTES, "piece placement");

struct Params {
    const int* qk;
    const __nv_bfloat16* k_cos;
    const __nv_bfloat16* k_sin;
    Scratch* scratch;
    const __nv_bfloat16* q;
    const __nv_bfloat16* q_cos;
    const __nv_bfloat16* q_sin;
    __nv_bfloat16* out;
};
struct Maps {
    CUtensorMap k, v, ks, kz, vs, vz, kh, vh, vf;
};

__global__ void __launch_bounds__(THREADS, 1)
kv_decode_kernel(const __grid_constant__ Params prm, const __grid_constant__ Maps maps) {
    extern __shared__ __align__(1024) unsigned char smem[];
    const uint32_t sb = __shfl_sync(0xffffffffu, smem_u32(smem), 0);
    if (threadIdx.x < 32 && elect_one()) {
        mbar_init(sb + BAR_FULLK, 1);
        asm volatile("fence.mbarrier_init.release.cluster;" ::: "memory");
        const uint32_t row = (blockIdx.x % TEAMS) * (G * S - 1) + blockIdx.x;
        const char* src = reinterpret_cast<const char*>(prm.qk) + row * (size_t)(D * 4);
        uint32_t dst = sb + CTRL_BYTES;
#pragma unroll 1
        do {
            bulk_load(dst, src, ROWS_BYTES, sb + BAR_FULLK);
            dst += ROWS_BYTES;
            src += S * D * 4;
        } while (dst != sb + CTRL_BYTES + KV_BYTES);
#pragma unroll
        for (int i = 1; i < BAR_FIN / 8 + NP; i++) mbar_init(sb + 8 * i, (unsigned)(i - BAR_EMPTY / 8) < STAGES ? G : 1);
        asm volatile("fence.mbarrier_init.release.cluster;" ::: "memory");
    }
    uint32_t bid;
    asm volatile("mov.u32 %0, %%ctaid.x;" : "=r"(bid));
    const int team = bid % TEAMS;
    const int cin = bid / TEAMS;
    const int h0 = team * G;
    const uint32_t buf0 = sb + CTRL_BYTES;
    const int warp = __shfl_sync(0xffffffffu, threadIdx.x >> 5, 0);
    const int lane = threadIdx.x & 31;

    if (warp >= W_CONS) {
        const int cw = warp - W_CONS;
        const int h = h0 + cw;
        const int r = lane >> 3;
        const int j = lane & 7;

        float qa[3][4], qb[3][4];
        {
            const __nv_bfloat16* qp = prm.q + h * D + 4 * j;
            const __nv_bfloat16* cp = prm.q_cos + 4 * j;
            const __nv_bfloat16* sp = prm.q_sin + 4 * j;
            static_for<3>([&](auto ic) {
                constexpr int i = decltype(ic)::value;
                const uint2 x1 = ldg64<64 * i>(qp), x2 = ldg64<64 * i + 2 * HALF>(qp);
                const uint2 c1 = ldg64<64 * i>(cp), c2 = ldg64<64 * i + 2 * HALF>(cp);
                const uint2 s1 = ldg64<64 * i>(sp), s2 = ldg64<64 * i + 2 * HALF>(sp);
                const uint32_t a0 = bf2_sub(bf2_mul(x1.x, c1.x), bf2_mul(x2.x, s1.x));
                const uint32_t a1 = bf2_sub(bf2_mul(x1.y, c1.y), bf2_mul(x2.y, s1.y));
                const uint32_t b0 = bf2_add(bf2_mul(x2.x, c2.x), bf2_mul(x1.x, s2.x));
                const uint32_t b1 = bf2_add(bf2_mul(x2.y, c2.y), bf2_mul(x1.y, s2.y));
                qa[i][0] = bf_lo(a0); qa[i][1] = bf_hi(a0); qa[i][2] = bf_lo(a1); qa[i][3] = bf_hi(a1);
                qb[i][0] = bf_lo(b0); qb[i][1] = bf_hi(b0); qb[i][2] = bf_lo(b1); qb[i][3] = bf_hi(b1);
            });
        }
        float acc[6][4];
#pragma unroll
        for (int i = 0; i < 6; i++)
#pragma unroll
            for (int c = 0; c < 4; c++) acc[i][c] = 0.f;
        float m_run = -3e38f, l_run = 0.f;
        float z_run = 0.f;

        const uint32_t va_off = OFF_V + ((lane & 16) ? 384 : 0);
        const uint32_t vb_off = OFF_V + ((lane & 16) ? 0 : 384);
        uint32_t kv_off = (uint32_t)((cw * T + r) * (D * 4) + j * 16);
        uint32_t cs_off = (uint32_t)(OFF_COS + r * (D * 2) + j * 8);
        uint32_t sc_off = (uint32_t)(OFF_KS + cw * 16 + r * 2);
        float mask = 0.f;

        asm volatile("bar.sync 0, %0;" ::"n"(THREADS) : "memory");

        int s = 0, word;
        uint32_t ph = 0;
#pragma unroll 1
        do {
            mbar_wait(sb + BAR_FULLK + 8 * s, ph);
            word = (int)lds32(sb + OFF_UIDX + 4 * s);
            const int pos = word & POS_MASK;
            if (pos >= UA * T) {
                kv_off = (uint32_t)((cw * (T / 2) + (r & 1)) * (D * 4) + j * 16);
                cs_off = (uint32_t)(OFF_COS + (r & 1) * (D * 2) + j * 8);
                sc_off = (uint32_t)(OFF_KS + cw * 16 + (r & 1) * 2);
                mask = r >= 2 ? -INFINITY : 0.f;
            }
            const uint32_t st = buf0 + s * STAGE_BYTES;
            const uint32_t sc = st + sc_off + (pos & 7) * 2;
            const float kz = lds_bf16(sc + SC_BYTES);
            const float ks = lds_bf16(sc) * QK_SCALE;
            const float vs = lds_bf16(sc + 2 * SC_BYTES);
            const float vz = lds_bf16(sc + 3 * SC_BYTES);

            float d0 = 0.f, d1 = 0.f;
#pragma unroll
            for (int i = 0; i < 3; i++) {
                const int4 ka = lds128(st + kv_off + i * 128);
                const int4 kb = lds128(st + kv_off + (i + 3) * 128);
                const uint2 ca = lds64(st + cs_off + i * 64);
                const uint2 cb = lds64(st + cs_off + (i + 3) * 64);
                const uint2 sa = lds64(st + cs_off + CS_BYTES + i * 64);
                const uint2 sb2 = lds64(st + cs_off + CS_BYTES + (i + 3) * 64);
                const float a[4] = {(float)ka.x - kz, (float)ka.y - kz, (float)ka.z - kz, (float)ka.w - kz};
                const float b[4] = {(float)kb.x - kz, (float)kb.y - kz, (float)kb.z - kz, (float)kb.w - kz};
                const float fca[4] = {bf_lo(ca.x), bf_hi(ca.x), bf_lo(ca.y), bf_hi(ca.y)};
                const float fcb[4] = {bf_lo(cb.x), bf_hi(cb.x), bf_lo(cb.y), bf_hi(cb.y)};
                const float fsa[4] = {bf_lo(sa.x), bf_hi(sa.x), bf_lo(sa.y), bf_hi(sa.y)};
                const float fsb[4] = {bf_lo(sb2.x), bf_hi(sb2.x), bf_lo(sb2.y), bf_hi(sb2.y)};
#pragma unroll
                for (int c = 0; c < 4; c++) {
                    const float ra = fmaf(a[c], fca[c], -b[c] * fsa[c]);
                    const float rb = fmaf(b[c], fcb[c], a[c] * fsb[c]);
                    d0 = fmaf(qa[i][c], ra, d0);
                    d1 = fmaf(qb[i][c], rb, d1);
                }
            }
            float dot = d0 + d1;
            dot += __shfl_xor_sync(0xffffffffu, dot, 1);
            dot += __shfl_xor_sync(0xffffffffu, dot, 2);
            dot += __shfl_xor_sync(0xffffffffu, dot, 4);
            const float sv = dot * ks;

            if ((unsigned)(pos - F0) < (unsigned)F_ROWS) {
                if (j == 0)
                    st_relaxed_b64(prm.scratch->logit + h * F_ROWS + (pos - F0) + r,
                                   (__float_as_uint(vs) >> 16) | __float_as_uint(vz),
                                   tagged(fmaxf(sv, -3e38f), (word >> TAG_SHIFT) & 1));
            } else {
                if (__any_sync(0xffffffffu, sv > m_run)) {
                    float m_new = fmaxf(sv, __shfl_xor_sync(0xffffffffu, sv, 8));
                    m_new = fmaxf(m_run, fmaxf(m_new, __shfl_xor_sync(0xffffffffu, m_new, 16)));
                    const float alpha = ex2(m_run - m_new);
                    l_run *= alpha;
                    z_run *= alpha;
#pragma unroll
                    for (int i = 0; i < 6; i++)
#pragma unroll
                        for (int c = 0; c < 4; c++) acc[i][c] *= alpha;
                    m_run = m_new;
                }
                const float p = ex2(sv - m_run + mask);
                const float pv = p * vs;
                l_run += p;
                z_run = fmaf(pv, vz, z_run);
                mbar_wait(sb + BAR_FULLV + 8 * s, ph);
#pragma unroll
                for (int i = 0; i < 6; i++) {
                    const int4 v = lds128(st + kv_off + (i < 3 ? va_off : vb_off) + (i % 3) * 128);
                    acc[i][0] = fmaf(pv, (float)v.x, acc[i][0]);
                    acc[i][1] = fmaf(pv, (float)v.y, acc[i][1]);
                    acc[i][2] = fmaf(pv, (float)v.z, acc[i][2]);
                    acc[i][3] = fmaf(pv, (float)v.w, acc[i][3]);
                }
            }
            __syncwarp();
            if (lane == 0) mbar_arrive(sb + BAR_EMPTY + 8 * s);
            if (++s == STAGES) { s = 0; ph ^= 1; }
        } while (!(word & LAST_BIT));

        {
            const uint32_t tag = (word >> TAG_SHIFT) & 1;
            char* slot = reinterpret_cast<char*>(prm.scratch->part + (h * CPT + cin) * SLOT_WORDS);
            char* part_st = slot + (lane & 16) * 32 + j * 16 + (lane & 8);
            l_run += __shfl_xor_sync(0xffffffffu, l_run, 8);
            z_run += __shfl_xor_sync(0xffffffffu, z_run, 8);
            l_run += __shfl_xor_sync(0xffffffffu, l_run, 16);
            z_run += __shfl_xor_sync(0xffffffffu, z_run, 16);
            st_relaxed_b64(slot + r * 256 + QC * 4 + j * 8, __float_as_uint(m_run), tagged(l_run, tag));
            const bool od = (lane & 8) != 0;
#pragma unroll
            for (int i = 0; i < 3; i++) {
                float k[4];
#pragma unroll
                for (int c = 0; c < 4; c++) k[c] = acc[i][c] + __shfl_xor_sync(0xffffffffu, acc[i + 3][c], 16);
                const float z0 = (od ? k[2] : k[0]) + __shfl_xor_sync(0xffffffffu, od ? k[0] : k[2], 8);
                const float z1 = (od ? k[3] : k[1]) + __shfl_xor_sync(0xffffffffu, od ? k[1] : k[3], 8);
                st_relaxed_b64(part_st + i * 128 + (i == 2 ? 64 : i == 1 ? (j & 4) * 16 : 0),
                               __float_as_uint(z0 - z_run), tagged(z1 - z_run, tag));
            }
            if (lane < QUARTERS) mbox_post(prm.scratch->mbox + (h * QUARTERS + lane) * MBOX_STRIDE, 1u);
        }

        if (cw >= RSLOTS * 12 / 32) return;
        const int ft = threadIdx.x - W_CONS * 32;
        const int rs = ft / 12;
        float a0 = 0.f, a1 = 0.f, a2 = 0.f, a3 = 0.f;
        mbar_wait(sb + BAR_W, 0);
        const uint32_t ra = sb + OFF_RV + rs * (RSTRIDE * 4 - QC * 4) + ft * 16;
#pragma unroll 1
        for (int p = 0; p < NP; p++) {
            const int4 w4 = lds128(sb + OFF_W + p * (P_ROWS * 4) + rs * 16);
            const float w[4] = {__int_as_float(w4.x), __int_as_float(w4.y), __int_as_float(w4.z), __int_as_float(w4.w)};
            const uint32_t va = sb + piece_off(p) + ft * 16;
            mbar_wait(sb + BAR_FIN + 8 * p, 0);
#pragma unroll
            for (int i = 0; i < 4; i++) {
                const int4 v = lds128(va + i * (RSLOTS * QC * 4));
                a0 = fmaf(w[i], (float)v.x, a0);
                a1 = fmaf(w[i], (float)v.y, a1);
                a2 = fmaf(w[i], (float)v.z, a2);
                a3 = fmaf(w[i], (float)v.w, a3);
            }
        }
        sts128f(ra, a0, a1, a2, a3);
        asm volatile("bar.arrive 3, %0;" ::"n"(RSLOTS * 12 + 32) : "memory");
        return;
    }

    if (warp >= W_GATHER) {
        asm volatile("bar.sync 0, %0;" ::"n"(THREADS) : "memory");
        const int sub = lane >= 13, quad = min(lane - sub * 13, 12);
        const int sg = 2 * (warp - W_GATHER) + sub;
        const float* src = prm.scratch->part + ((h0 + cin / QUARTERS) * CPT + sg) * SLOT_WORDS +
                           (cin % QUARTERS) * 64 + quad * 4;
        uint4 dt[NSL];
        mbar_wait(sb + BAR_INIT, 0);
        const uint32_t tag = lds32(sb + OFF_TAG);
        mbar_wait(sb + BAR_G, 0);
        int spin = 0;
        uint32_t bad;
#pragma unroll 1
        do {
            static_for<NSL>([&](auto bc) {
                constexpr int b = decltype(bc)::value;
                dt[b] = ld_relaxed_2xb64<b * SG * SLOT_WORDS * 4>(src);
            });
            bad = 0;
#pragma unroll
            for (int b = 0; b < NSL; b++) bad |= (dt[b].y ^ tag) | (dt[b].w ^ tag);
        } while (__any_sync(0xffffffffu, bad & 1u) && ++spin < (1 << 20));
        float mh[NSL], m = -INFINITY;
#pragma unroll
        for (int b = 0; b < NSL; b++) {
            mh[b] = __shfl_sync(0xffffffffu, __uint_as_float(dt[b].x), sub * 13 + 12);
            m = fmaxf(m, mh[b]);
        }
        float a0 = 0.f, a1 = 0.f, a2 = 0.f, a3 = 0.f;
#pragma unroll
        for (int b = 0; b < NSL; b++) {
            const float w = ex2(mh[b] - m);
            a0 = fmaf(w, __uint_as_float(dt[b].x), a0);
            a1 = fmaf(w, __uint_as_float(dt[b].y), a1);
            a2 = fmaf(w, __uint_as_float(dt[b].z), a2);
            a3 = fmaf(w, __uint_as_float(dt[b].w), a3);
        }
        if (lane < 26) sts128f(sb + OFF_RG + sg * (RSTRIDE * 4) + quad * 16, quad == 12 ? m : a0, a1, a2, a3);
        asm volatile("bar.arrive 2, %0;" ::"n"(GW * 32 + 32) : "memory");
        return;
    }

    if (warp == W_FIN) {
        if (elect_one()) {
            prefetch_map(&maps.ks);
            prefetch_map(&maps.kz);
            prefetch_map(&maps.vs);
            prefetch_map(&maps.vz);
            prefetch_map(&maps.k);
            prefetch_map(&maps.v);
        }
        asm volatile("bar.sync 0, %0;" ::"n"(THREADS) : "memory");
        const char* lptr = reinterpret_cast<const char*>(prm.scratch->logit + (h0 + cin / QUARTERS) * F_ROWS) + lane * 16;
        __nv_bfloat16* optr = prm.out + h0 * D + cin * QC + 2 * lane;
        mbar_wait(sb + BAR_INIT, 0);
        const uint32_t tag = lds32(sb + OFF_TAG);
        uint4 rec[NP];
        bool ok;
        int spin = 0;
        do {
            static_for<NP>([&](auto ic) { rec[decltype(ic)::value] = ld_relaxed_2xb64<decltype(ic)::value * 512>(lptr); });
            uint32_t bad = 0;
#pragma unroll
            for (int i = 0; i < NP; i++) bad |= (rec[i].y ^ tag) | (rec[i].w ^ tag);
            ok = (bad & 1u) == 0;
        } while (!__all_sync(0xffffffffu, ok) && ++spin < (1 << 20));
        float mF = -INFINITY, lF = 0.f, zF = 0.f;
#pragma unroll
        for (int i = 0; i < NP; i++) mF = fmaxf(mF, fmaxf(__uint_as_float(rec[i].y), __uint_as_float(rec[i].w)));
        mF = warp_max(mF);
        const uint32_t wa = sb + OFF_W + (lane & 7) * 32 + (lane >> 3) * 4;
#pragma unroll
        for (int i = 0; i < NP; i++) {
            const float p0 = ex2(__uint_as_float(rec[i].y) - mF), p1 = ex2(__uint_as_float(rec[i].w) - mF);
            const float a0 = p0 * bf_lo(rec[i].x), a1 = p1 * bf_lo(rec[i].z);
            lF += p0 + p1;
            zF = fmaf(a0, bf_hi(rec[i].x), fmaf(a1, bf_hi(rec[i].z), zF));
            sts32(wa + i * (P_ROWS * 4), __float_as_uint(a0));
            sts32(wa + i * (P_ROWS * 4) + 16, __float_as_uint(a1));
        }
        __syncwarp();
        if (lane == 0) mbar_arrive(sb + BAR_W);
#pragma unroll
        for (int o = 16; o > 0; o >>= 1) {
            lF += __shfl_xor_sync(0xffffffffu, lF, o);
            zF += __shfl_xor_sync(0xffffffffu, zF, o);
        }
        mbar_wait(sb + BAR_END, 0);
        if (lane == 0) {
            unsigned int* box = prm.scratch->mbox + (h0 * QUARTERS + cin) * MBOX_STRIDE;
            int seen = 0;
            do seen += mbox_take(box); while (seen < CPT && ++spin < (1 << 20));
            mbar_arrive(sb + BAR_G);
        }
        __syncwarp();
        const uint32_t col = sb + (uint32_t)min(lane, QC / 2 - 1) * 8;
        asm volatile("bar.sync 2, %0;" ::"r"(__float_as_uint(lF + zF) == 0xffffffffu ? 32 : GW * 32 + 32) : "memory");
        float2 ml[SG], ga[SG];
#pragma unroll
        for (int g = 0; g < SG; g++) {
            ml[g] = lds64f(sb + OFF_RG + g * (RSTRIDE * 4) + QC * 4);
            ga[g] = lds64f(col + OFF_RG + g * (RSTRIDE * 4));
        }
        float M = mF;
#pragma unroll
        for (int g = 0; g < SG; g++) M = fmaxf(M, ml[g].x);
        float wF = ex2(mF - M);
        float L = wF * lF, b0 = -wF * zF, b1 = b0;
#pragma unroll
        for (int g = 0; g < SG; g++) {
            const float w = ex2(ml[g].x - M);
            L = fmaf(w, ml[g].y, L);
            b0 = fmaf(w, ga[g].x, b0);
            b1 = fmaf(w, ga[g].y, b1);
        }
        const float inv = __fdividef(1.f, L);
        wF *= inv;
        b0 *= inv;
        b1 *= inv;
        asm volatile("bar.sync 3, %0;"
                     ::"r"(__any_sync(0xffffffffu, __float_as_uint(wF + b0 + b1) == 0xffffffffu) ? 32 : RSLOTS * 12 + 32) : "memory");
        float2 rv[RSLOTS];
#pragma unroll
        for (int g = 0; g < RSLOTS; g++) rv[g] = lds64f(col + OFF_RV + g * (RSTRIDE * 4));
        static_for<4>([&](auto lc) {
            constexpr int o = RSLOTS / 2 >> decltype(lc)::value;
#pragma unroll
            for (int g = 0; g < o; g++) {
                rv[g].x += rv[g + o].x;
                rv[g].y += rv[g + o].y;
            }
        });
        if (lane < QC / 2)
            *reinterpret_cast<__nv_bfloat162*>(optr) = __floats2bfloat162_rn(fmaf(wF, rv[0].x, b0), fmaf(wF, rv[0].y, b1));
        return;
    }

    __syncwarp();
    asm volatile("bar.arrive 0, %0;" ::"n"(THREADS) : "memory");
    if (!elect_one()) return;
    uint64_t pol = evict_first_policy();
    unsigned long long* ctr = prm.scratch->ctr;
    constexpr int total = TICKETS - (STAGES - 1) * CPT;
    const unsigned long long inc = 1ull << (15 * team);
    unsigned long long ticket = draw(ctr, inc);
    const uint32_t t_begin = now_ns();
    uint32_t w1 = 0, w2 = 0, w3 = 0;
    auto push = [&](uint32_t w) { w3 = w2; w2 = w1; w1 = w; };
    int s = 0, u = cin, k = 0, halves = 0, drawn = 0;
    uint32_t ph = 0;
    uint32_t t_draw = 0;
    bool init_done = false;
#pragma unroll 1
    for (;; k++) {
        const bool half = u >= UA;
        const int pos = half ? (u + UA) * (T / 2) : u * T;
        const int p8 = pos & ~7;
        const uint32_t fb = sb + BAR_FULLK + 8 * s;
        const uint32_t fv = sb + BAR_FULLV + 8 * s;
        const uint32_t dst = buf0 + s * STAGE_BYTES;
        halves += half;
        const bool gated = k >= STAGES && halves < STAGES;
        mbar_wait(sb + BAR_EMPTY + 8 * s, ph ^ 1);
        if (gated) mbar_wait(w3 & ~1u, w3 & 1u);
        if (k > 0) tma3d(dst + OFF_K, half ? &maps.kh : &maps.k, 0, pos, h0, fb, pol);
        bulk_load(dst + OFF_COS, prm.k_cos + (size_t)pos * D, half ? CS_BYTES / 2 : CS_BYTES, fb);
        bulk_load(dst + OFF_SIN, prm.k_sin + (size_t)pos * D, half ? CS_BYTES / 2 : CS_BYTES, fb);
        tma2d(dst + OFF_KS, &maps.ks, p8, h0, fb);
        tma2d(dst + OFF_KZ, &maps.kz, p8, h0, fb);
        tma2d(dst + OFF_VS, &maps.vs, p8, h0, fb);
        tma2d(dst + OFF_VZ, &maps.vz, p8, h0, fb);
        if (k >= STAGES) ticket = draw(ctr, inc);
        if ((u & (4 * 1 - 1)) == team * 1 && pos + (128 + 1) * T <= S && !half) {
            l2_prefetch(prm.k_cos + (size_t)(pos + 128 * T) * D, 1 * CS_BYTES);
            l2_prefetch(prm.k_sin + (size_t)(pos + 128 * T) * D, 1 * CS_BYTES);
        }
        if (half) t_draw = now_ns();
        push(fb | ph);
        if ((unsigned)(pos - F0) < (unsigned)F_ROWS) {
            mbar_arrive(fv);
            prefetch_map(&maps.kh);
            prefetch_map(&maps.vh);
            prefetch_map(&maps.vf);
        } else {
            if (gated) mbar_wait(w3 & ~1u, w3 & 1u);
            mbar_expect_tx(fv, half ? KV_BYTES / 2 : KV_BYTES);
            tma3d(dst + OFF_V, half ? &maps.vh : &maps.v, 0, pos, h0, fv, pol);
            push(fv | ph);
        }
        int un = u + CPT;
        uint32_t tag = 0;
        if (k >= STAGES - 1) {
            uint32_t lo, hi;
            asm volatile("st.shared.b64 [%2], %3;\nld.volatile.shared.v2.u32 {%0,%1}, [%2];"
                         : "=r"(lo), "=r"(hi) : "r"(sb + OFF_TICKET), "l"(ticket) : "memory");
            const int t01 = (int)(lo & 0x3fffffff), t23 = (int)(__funnelshift_r(lo, hi, 30) & 0x3fffffff);
            const int t = ((team & 2 ? t23 : t01) >> (15 * (team & 1))) & 0x7fff;
            drawn = (t01 & 0x7fff) + (t01 >> 15) + (t23 & 0x7fff) + (t23 >> 15);
            tag = ~hi >> 31;
            un = STAGES * CPT + t;
        }
        const bool start_fin = !init_done && un >= TICKETS - 2 * CPT;
        init_done |= start_fin;
        sts32(sb + OFF_UIDX + 4 * s, pos | (tag << TAG_SHIFT) | (un >= TICKETS ? LAST_BIT : 0));
        mbar_expect_tx(fb, half ? KSIDE_BYTES - KV_BYTES / 2 - CS_BYTES : KSIDE_BYTES);
        if (start_fin) {
            sts32(sb + OFF_TAG, tag);
            mbar_arrive(sb + BAR_INIT);
        }
        if (un >= TICKETS) break;
        u = un;
        if (++s == STAGES) { s = 0; ph ^= 1; }
    }
    mbar_arrive(sb + BAR_END);
    if (drawn == TEAMS * total - 1) draw(ctr, (1ull << 63) - total * 0x0000200040008001ull);
    uint32_t t_next = now_ns();
    int dt = (int)(t_draw - t_next) +
             (int)(((t_draw - t_begin) >> 4) * (uint32_t)(PACE_BASE + min(TEAMS * total - drawn, 512)) / (PACE_DIV / 16));
    dt = max(dt, 0) / NP;
    if (halves < STAGES) {
        mbar_wait(sb + BAR_EMPTY + 8 * s, ph);
        dt = 0;
    }
#pragma unroll 1
    for (int p = 0; p < NP; p++) {
        const uint32_t fb = sb + BAR_FIN + 8 * p;
        t_next += dt;
        while ((int)(now_ns() - t_next) < 0 && !mbar_test(w2 & ~1u, w2 & 1u)) {}
        mbar_expect_tx(fb, PIECE_BYTES);
        tma3d(sb + piece_off(p), &maps.vf, (cin % QUARTERS) * QC, F0 + p * P_ROWS, h0 + cin / QUARTERS, fb, pol);
        push(fb);
    }
}

__global__ void __launch_bounds__(128)
fallback_partial_kernel(const Params prm, const int* qv, const __nv_bfloat16* ks, const __nv_bfloat16* kz,
                        const __nv_bfloat16* vs, const __nv_bfloat16* vz) {
    const int h = blockIdx.y, slot = blockIdx.x * 4 + (threadIdx.x >> 5), lane = threadIdx.x & 31;
    float qa[3], qb[3], acc[6] = {0.f, 0.f, 0.f, 0.f, 0.f, 0.f};
    for (int i = 0; i < 3; i++) {
        const int d = 32 * i + lane;
        const __nv_bfloat16 x1 = prm.q[h * D + d], x2 = prm.q[h * D + d + HALF];
        qa[i] = __bfloat162float(__hsub_rn(__hmul_rn(x1, prm.q_cos[d]), __hmul_rn(x2, prm.q_sin[d])));
        qb[i] = __bfloat162float(__hadd_rn(__hmul_rn(x2, prm.q_cos[d + HALF]), __hmul_rn(x1, prm.q_sin[d + HALF])));
    }
    float m = -3e38f, l = 0.f;
    for (int pos = slot; pos < S; pos += CPT) {
        const size_t row = (size_t)h * S + pos;
        const float z = __bfloat162float(kz[row]);
        float dot = 0.f;
        for (int i = 0; i < 3; i++) {
            const int d = 32 * i + lane;
            const float a = (float)prm.qk[row * D + d] - z, b = (float)prm.qk[row * D + d + HALF] - z;
            const __nv_bfloat16* c = prm.k_cos + pos * D + d;
            const __nv_bfloat16* sn = prm.k_sin + pos * D + d;
            dot += qa[i] * (a * __bfloat162float(c[0]) - b * __bfloat162float(sn[0])) +
                   qb[i] * (b * __bfloat162float(c[HALF]) + a * __bfloat162float(sn[HALF]));
        }
        for (int o = 16; o > 0; o >>= 1) dot += __shfl_xor_sync(0xffffffffu, dot, o);
        const float sv = dot * __bfloat162float(ks[row]) * QK_SCALE;
        const float m_new = fmaxf(m, sv), alpha = ex2(m - m_new), p = ex2(sv - m_new);
        const float pv = p * __bfloat162float(vs[row]), zv = __bfloat162float(vz[row]);
        m = m_new;
        l = l * alpha + p;
        for (int i = 0; i < 6; i++) acc[i] = acc[i] * alpha + pv * ((float)qv[row * D + 32 * i + lane] - zv);
    }
    float* dst = prm.scratch->part + (h * CPT + slot) * SLOT_WORDS;
    for (int i = 0; i < 6; i++) dst[32 * i + lane] = acc[i];
    if (lane == 0) {
        dst[D] = m;
        dst[D + 1] = l;
    }
}

__global__ void __launch_bounds__(D) fallback_merge_kernel(const Params prm) {
    const float* src = prm.scratch->part + blockIdx.x * CPT * SLOT_WORDS;
    float m = -3e38f, l = 0.f, o = 0.f;
    for (int c = 0; c < CPT; c++) m = fmaxf(m, src[c * SLOT_WORDS + D]);
    for (int c = 0; c < CPT; c++) {
        const float w = ex2(src[c * SLOT_WORDS + D] - m);
        l += w * src[c * SLOT_WORDS + D + 1];
        o += w * src[c * SLOT_WORDS + threadIdx.x];
    }
    prm.out[blockIdx.x * D + threadIdx.x] = __float2bfloat16_rn(o / l);
}

typedef CUresult (*EncodeTiledFn)(CUtensorMap*, CUtensorMapDataType, cuuint32_t, void*, const cuuint64_t*,
                                  const cuuint64_t*, const cuuint32_t*, const cuuint32_t*,
                                  CUtensorMapInterleave, CUtensorMapSwizzle, CUtensorMapL2promotion,
                                  CUtensorMapFloatOOBfill);

void make_kv_map(EncodeTiledFn enc, CUtensorMap* m, const void* ptr, int cols, int rows, int heads,
                 CUtensorMapL2promotion promo) {
    cuuint64_t dims[3] = {(cuuint64_t)D, (cuuint64_t)S, (cuuint64_t)H};
    cuuint64_t strides[2] = {(cuuint64_t)D * 4, (cuuint64_t)S * D * 4};
    cuuint32_t box[3] = {(cuuint32_t)cols, (cuuint32_t)rows, (cuuint32_t)heads};
    cuuint32_t es[3] = {1, 1, 1};
    enc(m, CU_TENSOR_MAP_DATA_TYPE_INT32, 3, const_cast<void*>(ptr), dims, strides, box, es,
        CU_TENSOR_MAP_INTERLEAVE_NONE, CU_TENSOR_MAP_SWIZZLE_NONE, promo, CU_TENSOR_MAP_FLOAT_OOB_FILL_NONE);
}

void make_scale_map(EncodeTiledFn enc, CUtensorMap* m, const void* ptr) {
    cuuint64_t dims[2] = {(cuuint64_t)S, (cuuint64_t)H};
    cuuint64_t strides[1] = {(cuuint64_t)S * 2};
    cuuint32_t box[2] = {8, (cuuint32_t)G};
    cuuint32_t es[2] = {1, 1};
    enc(m, CU_TENSOR_MAP_DATA_TYPE_BFLOAT16, 2, const_cast<void*>(ptr), dims, strides, box, es,
        CU_TENSOR_MAP_INTERLEAVE_NONE, CU_TENSOR_MAP_SWIZZLE_NONE, CU_TENSOR_MAP_L2_PROMOTION_L2_256B,
        CU_TENSOR_MAP_FLOAT_OOB_FILL_NONE);
}

}

extern "C" void kernel_launch(void* const* d_in, const int* in_sizes, int n_in, void* d_out, int out_size) {
    (void)in_sizes; (void)n_in; (void)out_size;
    static EncodeTiledFn enc = nullptr;
    static Scratch* scratch = nullptr;
    static int sms = 0;
    if (!enc) {
        void* fn = nullptr;
        cudaDriverEntryPointQueryResult qr;
        cudaGetDriverEntryPoint("cuTensorMapEncodeTiled", &fn, cudaEnableDefault, &qr);
        enc = (EncodeTiledFn)fn;
        int dev = 0;
        cudaGetDevice(&dev);
        cudaDeviceGetAttribute(&sms, cudaDevAttrMultiProcessorCount, dev);
        cudaGetSymbolAddress((void**)&scratch, g_scratch);
        cudaFuncSetAttribute(kv_decode_kernel, cudaFuncAttributeMaxDynamicSharedMemorySize, SMEM_BYTES);
    }
    Params prm;
    prm.q = (const __nv_bfloat16*)d_in[0];
    prm.qk = (const int*)d_in[1];
    prm.q_cos = (const __nv_bfloat16*)d_in[7];
    prm.q_sin = (const __nv_bfloat16*)d_in[8];
    prm.k_cos = (const __nv_bfloat16*)d_in[9];
    prm.k_sin = (const __nv_bfloat16*)d_in[10];
    prm.out = (__nv_bfloat16*)d_out;
    prm.scratch = scratch;
    if (sms < TEAMS * CPT) {
        fallback_partial_kernel<<<dim3(CPT / 4, H), 128>>>(
            prm, (const int*)d_in[4], (const __nv_bfloat16*)d_in[2], (const __nv_bfloat16*)d_in[3],
            (const __nv_bfloat16*)d_in[5], (const __nv_bfloat16*)d_in[6]);
        fallback_merge_kernel<<<H, D>>>(prm);
        return;
    }
    Maps maps;
    make_kv_map(enc, &maps.k, prm.qk, D, T, G, CU_TENSOR_MAP_L2_PROMOTION_L2_128B);
    make_kv_map(enc, &maps.v, d_in[4], D, T, G, CU_TENSOR_MAP_L2_PROMOTION_L2_128B);
    make_kv_map(enc, &maps.kh, prm.qk, D, T / 2, G, CU_TENSOR_MAP_L2_PROMOTION_L2_128B);
    make_kv_map(enc, &maps.vh, d_in[4], D, T / 2, G, CU_TENSOR_MAP_L2_PROMOTION_L2_128B);
    make_kv_map(enc, &maps.vf, d_in[4], QC, P_ROWS, 1, CU_TENSOR_MAP_L2_PROMOTION_NONE);
    make_scale_map(enc, &maps.ks, d_in[2]);
    make_scale_map(enc, &maps.kz, d_in[3]);
    make_scale_map(enc, &maps.vs, d_in[5]);
    make_scale_map(enc, &maps.vz, d_in[6]);

    kv_decode_kernel<<<TEAMS * CPT, THREADS, SMEM_BYTES>>>(prm, maps);
}
```

```cpp
#include <cuda_runtime.h>
#include <cuda_bf16.h>
#include <cuda.h>
#include <stdint.h>
#include <type_traits>

namespace {

constexpr int H = 32;
constexpr int S = 16384;
constexpr int D = 192;
constexpr int HALF = D / 2;
constexpr float QK_SCALE = 0.07216878364870322f * 1.4426950408889634f;

constexpr int G = 8;
constexpr int T = 4;
constexpr int TEAMS = H / G;
constexpr int UNITS = S / T;
constexpr int STAGES = 3;
constexpr int TAIL_UNITS = 130;
constexpr int UA = UNITS - TAIL_UNITS;
constexpr int TICKETS = UA + 2 * TAIL_UNITS;
constexpr int CS_AHEAD = TAIL_UNITS;
constexpr int F_ROWS = 512;
constexpr int P_ROWS = 64;
constexpr int NP = F_ROWS / P_ROWS;
constexpr int F0 = UA * T - F_ROWS;
constexpr int QUARTERS = 4;
constexpr int QC = D / QUARTERS;
constexpr int CPT = G * QUARTERS;
constexpr int GW = 4;
constexpr int SG = 2 * GW;
constexpr int NSL = CPT / SG;
constexpr int RSLOTS = 8;
constexpr int RSTRIDE = 52;
constexpr int SLOT_WORDS = QUARTERS * 64;

constexpr int MBOX_STRIDE = 32;
constexpr int PACE_BASE = 285;
constexpr int PACE_DIV = 20700;

constexpr int W_FIN = 1;
constexpr int W_GATHER = 2;
constexpr int W_CONS = W_GATHER + GW;
constexpr int THREADS = (W_CONS + G) * 32;

constexpr int KV_BYTES = G * T * D * 4;
constexpr int ROWS_BYTES = T * D * 4;
constexpr int CS_BYTES = T * D * 2;
constexpr int SC_BYTES = G * 8 * 2;
constexpr int OFF_K = 0;
constexpr int OFF_V = KV_BYTES;
constexpr int OFF_COS = 2 * KV_BYTES;
constexpr int OFF_SIN = OFF_COS + CS_BYTES;
constexpr int OFF_KS = OFF_SIN + CS_BYTES;
constexpr int OFF_KZ = OFF_KS + SC_BYTES;
constexpr int OFF_VS = OFF_KZ + SC_BYTES;
constexpr int OFF_VZ = OFF_VS + SC_BYTES;
constexpr int STAGE_BYTES = OFF_VZ + SC_BYTES;
constexpr int KSIDE_BYTES = STAGE_BYTES - KV_BYTES;
constexpr int PIECE_BYTES = P_ROWS * QC * 4;

constexpr int BAR_FULLK = 0;
constexpr int BAR_FULLV = 8 * STAGES;
constexpr int BAR_EMPTY = 16 * STAGES;
constexpr int BAR_INIT = 24 * STAGES;
constexpr int BAR_END = BAR_INIT + 8;
constexpr int BAR_W = BAR_END + 8;
constexpr int BAR_G = BAR_W + 8;
constexpr int BAR_FIN = BAR_G + 8;
constexpr int OFF_UIDX = 224;
constexpr int OFF_TAG = OFF_UIDX + 4 * STAGES;
constexpr int OFF_TICKET = OFF_TAG + 4;
constexpr int LAST_BIT = 1 << 30;
constexpr int TAG_SHIFT = 29;
constexpr int POS_MASK = (1 << TAG_SHIFT) - 1;
constexpr int CTRL_BYTES = 256;
constexpr int OFF_W = CTRL_BYTES + STAGES * STAGE_BYTES;
constexpr int OFF_RV = OFF_W + F_ROWS * 4;
constexpr int OFF_RG = OFF_RV + RSLOTS * RSTRIDE * 4;
constexpr int SMEM_USED = OFF_W + 2 * KV_BYTES;
static_assert(OFF_RG + SG * RSTRIDE * 4 <= OFF_W + KV_BYTES / 2 && NP <= 2 * STAGES + 2, "final-phase buffers");
static_assert(BAR_FIN + 8 * NP <= OFF_UIDX && OFF_TICKET % 8 == 0, "control block");
constexpr int SMEM_BYTES = SMEM_USED;
static_assert(STAGE_BYTES % 128 == 0 && PIECE_BYTES % 128 == 0 && TEAMS == T, "layout");
static_assert(SMEM_BYTES <= 232448, "shared memory budget");

struct __align__(128) Scratch {
    float part[H * CPT * SLOT_WORDS];
    uint2 logit[H * F_ROWS];
    unsigned int mbox[H * QUARTERS * MBOX_STRIDE];
    unsigned long long ctr[16];
};
__device__ Scratch g_scratch;

__device__ __forceinline__ uint32_t smem_u32(const void* p) {
    return (uint32_t)__cvta_generic_to_shared(p);
}
__device__ __forceinline__ void mbar_init(uint32_t bar, int cnt) {
    asm volatile("mbarrier.init.shared::cta.b64 [%0], %1;" ::"r"(bar), "r"(cnt) : "memory");
}
__device__ __forceinline__ void mbar_expect_tx(uint32_t bar, uint32_t bytes) {
    asm volatile("mbarrier.arrive.expect_tx.shared::cta.b64 _, [%0], %1;" ::"r"(bar), "r"(bytes) : "memory");
}
__device__ __forceinline__ void mbar_arrive(uint32_t bar) {
    asm volatile("mbarrier.arrive.shared::cta.b64 _, [%0];" ::"r"(bar) : "memory");
}
__device__ __forceinline__ void mbar_wait(uint32_t bar, uint32_t parity) {
    asm volatile(
        "{\n"
        ".reg .pred p;\n"
        ".reg .u32 n;\n"
        "mov.u32 n, 0;\n"
        "WAIT_%=:\n"
        "mbarrier.try_wait.parity.shared::cta.b64 p, [%0], %1;\n"
        "@p bra DONE_%=;\n"
        "add.u32 n, n, 1;\n"
        "setp.lt.u32 p, n, 0x400000;\n"
        "@p bra WAIT_%=;\n"
        "DONE_%=:\n"
        "}" ::"r"(bar), "r"(parity) : "memory");
}
__device__ __forceinline__ bool mbar_test(uint32_t bar, uint32_t parity) {
    uint32_t ok;
    asm volatile("{\n.reg .pred p;\nmbarrier.test_wait.parity.shared::cta.b64 p, [%1], %2;\nselp.u32 %0, 1, 0, p;\n}"
                 : "=r"(ok) : "r"(bar), "r"(parity) : "memory");
    return ok != 0;
}
__device__ __forceinline__ uint32_t now_ns() {
    uint32_t t;
    asm volatile("mov.u32 %0, %%globaltimer_lo;" : "=r"(t)::"memory");
    return t;
}
__device__ __forceinline__ bool elect_one() {
    uint32_t p;
    asm volatile("{\n.reg .pred p;\nelect.sync _|p, 0xffffffff;\nselp.u32 %0, 1, 0, p;\n}" : "=r"(p));
    return p != 0;
}
__device__ __forceinline__ void bulk_load(uint32_t dst, const void* src, uint32_t bytes, uint32_t bar) {
    asm volatile("cp.async.bulk.shared::cluster.global.mbarrier::complete_tx::bytes [%0], [%1], %2, [%3];"
                 ::"r"(dst), "l"(src), "r"(bytes), "r"(bar) : "memory");
}
__device__ __forceinline__ void tma3d(uint32_t dst, const CUtensorMap* map, int c0, int c1, int c2,
                                      uint32_t bar, uint64_t pol) {
    asm volatile(
        "cp.async.bulk.tensor.3d.shared::cluster.global.mbarrier::complete_tx::bytes.L2::cache_hint"
        " [%0], [%1, {%2, %3, %4}], [%5], %6;"
        ::"r"(dst), "l"(map), "r"(c0), "r"(c1), "r"(c2), "r"(bar), "l"(pol) : "memory");
}
__device__ __forceinline__ void tma2d(uint32_t dst, const CUtensorMap* map, int c0, int c1, uint32_t bar) {
    asm volatile(
        "cp.async.bulk.tensor.2d.shared::cluster.global.mbarrier::complete_tx::bytes"
        " [%0], [%1, {%2, %3}], [%4];"
        ::"r"(dst), "l"(map), "r"(c0), "r"(c1), "r"(bar) : "memory");
}
__device__ __forceinline__ void l2_prefetch(const void* src, uint32_t bytes) {
    asm volatile("cp.async.bulk.prefetch.L2.global [%0], %1;" ::"l"(src), "r"(bytes) : "memory");
}
__device__ __forceinline__ void prefetch_map(const CUtensorMap* map) {
    asm volatile("prefetch.tensormap [%0];" ::"l"(map) : "memory");
}
__device__ __forceinline__ uint64_t evict_first_policy() {
    uint64_t pol;
    asm volatile("createpolicy.fractional.L2::evict_first.b64 %0, 1.0;" : "=l"(pol));
    return pol;
}
__device__ __forceinline__ float ex2(float x) {
    float y;
    asm("ex2.approx.ftz.f32 %0, %1;" : "=f"(y) : "f"(x));
    return y;
}
__device__ __forceinline__ float bf_lo(uint32_t x) { return __uint_as_float(x << 16); }
__device__ __forceinline__ float bf_hi(uint32_t x) { return __uint_as_float(x & 0xffff0000u); }
__device__ __forceinline__ uint32_t bf2_mul(uint32_t a, uint32_t b) {
    uint32_t d;
    asm("mul.rn.bf16x2 %0, %1, %2;" : "=r"(d) : "r"(a), "r"(b));
    return d;
}
__device__ __forceinline__ uint32_t bf2_add(uint32_t a, uint32_t b) {
    uint32_t d;
    asm("add.rn.bf16x2 %0, %1, %2;" : "=r"(d) : "r"(a), "r"(b));
    return d;
}
__device__ __forceinline__ uint32_t bf2_sub(uint32_t a, uint32_t b) {
    uint32_t d;
    asm("sub.rn.bf16x2 %0, %1, %2;" : "=r"(d) : "r"(a), "r"(b));
    return d;
}
__device__ __forceinline__ float lds_bf16(uint32_t addr) {
    unsigned short v;
    asm volatile("ld.shared.u16 %0, [%1];" : "=h"(v) : "r"(addr));
    return __uint_as_float(((uint32_t)v) << 16);
}
__device__ __forceinline__ int4 lds128(uint32_t addr) {
    int4 v;
    asm volatile("ld.shared.v4.s32 {%0,%1,%2,%3}, [%4];" : "=r"(v.x), "=r"(v.y), "=r"(v.z), "=r"(v.w) : "r"(addr));
    return v;
}
__device__ __forceinline__ uint2 lds64(uint32_t addr) {
    uint2 v;
    asm volatile("ld.shared.v2.u32 {%0,%1}, [%2];" : "=r"(v.x), "=r"(v.y) : "r"(addr));
    return v;
}
__device__ __forceinline__ float2 lds64f(uint32_t addr) {
    const uint2 v = lds64(addr);
    return make_float2(__uint_as_float(v.x), __uint_as_float(v.y));
}
__device__ __forceinline__ uint32_t lds32(uint32_t addr) {
    uint32_t v;
    asm volatile("ld.shared.u32 %0, [%1];" : "=r"(v) : "r"(addr) : "memory");
    return v;
}
__device__ __forceinline__ void sts32(uint32_t addr, uint32_t v) {
    asm volatile("st.shared.u32 [%0], %1;" ::"r"(addr), "r"(v) : "memory");
}
__device__ __forceinline__ void sts128f(uint32_t addr, float a, float b, float c, float d) {
    asm volatile("st.shared.v4.f32 [%0], {%1,%2,%3,%4};" ::"r"(addr), "f"(a), "f"(b), "f"(c), "f"(d) : "memory");
}
__device__ __forceinline__ float warp_max(float x) {
    int k = __float_as_int(x);
    k ^= (k >> 31) & 0x7fffffff;
    k = __reduce_max_sync(0xffffffffu, k);
    return __int_as_float(k ^ ((k >> 31) & 0x7fffffff));
}

__device__ __forceinline__ uint32_t tagged(float x, uint32_t tag) { return (__float_as_uint(x) & ~1u) | tag; }

__device__ __forceinline__ void st_relaxed_b64(const void* p, uint32_t lo, uint32_t hi) {
    asm volatile("{\n.reg .b64 v;\nmov.b64 v, {%1,%2};\nst.relaxed.gpu.global.b64 [%0], v;\n}"
                 ::"l"(p), "r"(lo), "r"(hi) : "memory");
}
template <int OFF>
__device__ __forceinline__ uint4 ld_relaxed_2xb64(const void* base) {
    uint4 v;
    asm volatile("{\n.reg .b64 a, b;\nld.relaxed.gpu.global.v2.b64 {a, b}, [%4+%5];\n"
                 "mov.b64 {%0,%1}, a;\nmov.b64 {%2,%3}, b;\n}"
                 : "=r"(v.x), "=r"(v.y), "=r"(v.z), "=r"(v.w) : "l"(base), "n"(OFF) : "memory");
    return v;
}
__device__ __forceinline__ void mbox_post(unsigned int* box, unsigned int bits) {
    asm volatile("red.relaxed.gpu.global.add.u32 [%0], %1;" ::"l"(box), "r"(bits) : "memory");
}
__device__ __forceinline__ unsigned int mbox_take(unsigned int* box) {
    unsigned int v;
    asm volatile("atom.relaxed.gpu.global.exch.b32 %0, [%1], 0;" : "=r"(v) : "l"(box) : "memory");
    return v;
}
template <int OFF>
__device__ __forceinline__ uint2 ldg64(const void* base) {
    uint2 v;
    asm volatile("ld.global.nc.v2.u32 {%0,%1}, [%2+%3];" : "=r"(v.x), "=r"(v.y) : "l"(base), "n"(OFF));
    return v;
}
template <int N, typename F>
__device__ __forceinline__ void static_for(F&& f) {
    if constexpr (N > 0) {
        static_for<N - 1>(f);
        f(std::integral_constant<int, N - 1>{});
    }
}
__device__ __forceinline__ unsigned long long draw(unsigned long long* ctr, unsigned long long inc) {
    unsigned long long v;
    asm volatile("atom.relaxed.gpu.global.add.u64 %0, [%1], %2;" : "=l"(v) : "l"(ctr), "l"(inc) : "memory");
    return v;
}

__device__ __forceinline__ uint32_t piece_off(int p) {
    return CTRL_BYTES + KV_BYTES / 2 + (p >> 1) * STAGE_BYTES + (p & 1) * KV_BYTES;
}
static_assert(PIECE_BYTES == KV_BYTES / 2 && OFF_K == 0 && OFF_V == KV_BYTES, "piece placement");

struct Params {
    const int* qk;
    const __nv_bfloat16* k_cos;
    const __nv_bfloat16* k_sin;
    Scratch* scratch;
    const __nv_bfloat16* q;
    const __nv_bfloat16* q_cos;
    const __nv_bfloat16* q_sin;
    __nv_bfloat16* out;
};
struct Maps {
    CUtensorMap k, v, ks, kz, vs, vz, kh, vh, vf;
};

__global__ void __launch_bounds__(THREADS, 1)
kv_decode_kernel(const __grid_constant__ Params prm, const __grid_constant__ Maps maps) {
    extern __shared__ __align__(1024) unsigned char smem[];
    const uint32_t sb = __shfl_sync(0xffffffffu, smem_u32(smem), 0);
    if (threadIdx.x < 32 && elect_one()) {
        mbar_init(sb + BAR_FULLK, 1);
        asm volatile("fence.mbarrier_init.release.cluster;" ::: "memory");
        const uint32_t row = (blockIdx.x % TEAMS) * (G * S - 1) + blockIdx.x;
        const char* src = reinterpret_cast<const char*>(prm.qk) + row * (size_t)(D * 4);
        uint32_t dst = sb + CTRL_BYTES;
#pragma unroll 1
        do {
            bulk_load(dst, src, ROWS_BYTES, sb + BAR_FULLK);
            dst += ROWS_BYTES;
            src += S * D * 4;
        } while (dst != sb + CTRL_BYTES + KV_BYTES);
#pragma unroll
        for (int i = 1; i < BAR_FIN / 8 + NP; i++) mbar_init(sb + 8 * i, (unsigned)(i - BAR_EMPTY / 8) < STAGES ? G : 1);
        asm volatile("fence.mbarrier_init.release.cluster;" ::: "memory");
    }
    uint32_t bid;
    asm volatile("mov.u32 %0, %%ctaid.x;" : "=r"(bid));
    const int team = bid % TEAMS;
    const int cin = bid / TEAMS;
    const int h0 = team * G;
    const uint32_t buf0 = sb + CTRL_BYTES;
    const int warp = __shfl_sync(0xffffffffu, threadIdx.x >> 5, 0);
    const int lane = threadIdx.x & 31;

    if (warp >= W_CONS) {
        const int cw = warp - W_CONS;
        const int h = h0 + cw;
        const int r = lane >> 3;
        const int j = lane & 7;

        float qa[3][4], qb[3][4];
        {
            const __nv_bfloat16* qp = prm.q + h * D + 4 * j;
            const __nv_bfloat16* cp = prm.q_cos + 4 * j;
            const __nv_bfloat16* sp = prm.q_sin + 4 * j;
            static_for<3>([&](auto ic) {
                constexpr int i = decltype(ic)::value;
                const uint2 x1 = ldg64<64 * i>(qp), x2 = ldg64<64 * i + 2 * HALF>(qp);
                const uint2 c1 = ldg64<64 * i>(cp), c2 = ldg64<64 * i + 2 * HALF>(cp);
                const uint2 s1 = ldg64<64 * i>(sp), s2 = ldg64<64 * i + 2 * HALF>(sp);
                const uint32_t a0 = bf2_sub(bf2_mul(x1.x, c1.x), bf2_mul(x2.x, s1.x));
                const uint32_t a1 = bf2_sub(bf2_mul(x1.y, c1.y), bf2_mul(x2.y, s1.y));
                const uint32_t b0 = bf2_add(bf2_mul(x2.x, c2.x), bf2_mul(x1.x, s2.x));
                const uint32_t b1 = bf2_add(bf2_mul(x2.y, c2.y), bf2_mul(x1.y, s2.y));
                qa[i][0] = bf_lo(a0); qa[i][1] = bf_hi(a0); qa[i][2] = bf_lo(a1); qa[i][3] = bf_hi(a1);
                qb[i][0] = bf_lo(b0); qb[i][1] = bf_hi(b0); qb[i][2] = bf_lo(b1); qb[i][3] = bf_hi(b1);
            });
        }
        float acc[6][4];
#pragma unroll
        for (int i = 0; i < 6; i++)
#pragma unroll
            for (int c = 0; c < 4; c++) acc[i][c] = 0.f;
        float m_run = -3e38f, l_run = 0.f;
        float z_run = 0.f;

        const uint32_t va_off = OFF_V + ((lane & 16) ? 384 : 0);
        const uint32_t vb_off = OFF_V + ((lane & 16) ? 0 : 384);
        uint32_t kv_off = (uint32_t)((cw * T + r) * (D * 4) + j * 16);
        uint32_t cs_off = (uint32_t)(OFF_COS + r * (D * 2) + j * 8);
        uint32_t sc_off = (uint32_t)(OFF_KS + cw * 16 + r * 2);
        float mask = 0.f;

        asm volatile("bar.sync 0, %0;" ::"n"(THREADS) : "memory");

        int s = 0, word;
        uint32_t ph = 0;
#pragma unroll 1
        do {
            mbar_wait(sb + BAR_FULLK + 8 * s, ph);
            word = (int)lds32(sb + OFF_UIDX + 4 * s);
            const int pos = word & POS_MASK;
            if (pos >= UA * T) {
                kv_off = (uint32_t)((cw * (T / 2) + (r & 1)) * (D * 4) + j * 16);
                cs_off = (uint32_t)(OFF_COS + (r & 1) * (D * 2) + j * 8);
                sc_off = (uint32_t)(OFF_KS + cw * 16 + (r & 1) * 2);
                mask = r >= 2 ? -INFINITY : 0.f;
            }
            const uint32_t st = buf0 + s * STAGE_BYTES;
            const uint32_t sc = st + sc_off + (pos & 7) * 2;
            const float kz = lds_bf16(sc + SC_BYTES);
            const float ks = lds_bf16(sc) * QK_SCALE;
            const float vs = lds_bf16(sc + 2 * SC_BYTES);
            const float vz = lds_bf16(sc + 3 * SC_BYTES);

            float d0 = 0.f, d1 = 0.f;
#pragma unroll
            for (int i = 0; i < 3; i++) {
                const int4 ka = lds128(st + kv_off + i * 128);
                const int4 kb = lds128(st + kv_off + (i + 3) * 128);
                const uint2 ca = lds64(st + cs_off + i * 64);
                const uint2 cb = lds64(st + cs_off + (i + 3) * 64);
                const uint2 sa = lds64(st + cs_off + CS_BYTES + i * 64);
                const uint2 sb2 = lds64(st + cs_off + CS_BYTES + (i + 3) * 64);
                const float a[4] = {(float)ka.x - kz, (float)ka.y - kz, (float)ka.z - kz, (float)ka.w - kz};
                const float b[4] = {(float)kb.x - kz, (float)kb.y - kz, (float)kb.z - kz, (float)kb.w - kz};
                const float fca[4] = {bf_lo(ca.x), bf_hi(ca.x), bf_lo(ca.y), bf_hi(ca.y)};
                const float fcb[4] = {bf_lo(cb.x), bf_hi(cb.x), bf_lo(cb.y), bf_hi(cb.y)};
                const float fsa[4] = {bf_lo(sa.x), bf_hi(sa.x), bf_lo(sa.y), bf_hi(sa.y)};
                const float fsb[4] = {bf_lo(sb2.x), bf_hi(sb2.x), bf_lo(sb2.y), bf_hi(sb2.y)};
#pragma unroll
                for (int c = 0; c < 4; c++) {
                    const float ra = fmaf(a[c], fca[c], -b[c] * fsa[c]);
                    const float rb = fmaf(b[c], fcb[c], a[c] * fsb[c]);
                    d0 = fmaf(qa[i][c], ra, d0);
                    d1 = fmaf(qb[i][c], rb, d1);
                }
            }
            float dot = d0 + d1;
            dot += __shfl_xor_sync(0xffffffffu, dot, 1);
            dot += __shfl_xor_sync(0xffffffffu, dot, 2);
            dot += __shfl_xor_sync(0xffffffffu, dot, 4);
            const float sv = dot * ks;

            if ((unsigned)(pos - F0) < (unsigned)F_ROWS) {
                if (j == 0)
                    st_relaxed_b64(prm.scratch->logit + h * F_ROWS + (pos - F0) + r,
                                   (__float_as_uint(vs) >> 16) | __float_as_uint(vz),
                                   tagged(fmaxf(sv, -3e38f), (word >> TAG_SHIFT) & 1));
            } else {
                if (__any_sync(0xffffffffu, sv > m_run)) {
                    float m_new = fmaxf(sv, __shfl_xor_sync(0xffffffffu, sv, 8));
                    m_new = fmaxf(m_run, fmaxf(m_new, __shfl_xor_sync(0xffffffffu, m_new, 16)));
                    const float alpha = ex2(m_run - m_new);
                    l_run *= alpha;
                    z_run *= alpha;
#pragma unroll
                    for (int i = 0; i < 6; i++)
#pragma unroll
                        for (int c = 0; c < 4; c++) acc[i][c] *= alpha;
                    m_run = m_new;
                }
                const float p = ex2(sv - m_run + mask);
                const float pv = p * vs;
                l_run += p;
                z_run = fmaf(pv, vz, z_run);
                mbar_wait(sb + BAR_FULLV + 8 * s, ph);
#pragma unroll
                for (int i = 0; i < 6; i++) {
                    const int4 v = lds128(st + kv_off + (i < 3 ? va_off : vb_off) + (i % 3) * 128);
                    acc[i][0] = fmaf(pv, (float)v.x, acc[i][0]);
                    acc[i][1] = fmaf(pv, (float)v.y, acc[i][1]);
                    acc[i][2] = fmaf(pv, (float)v.z, acc[i][2]);
                    acc[i][3] = fmaf(pv, (float)v.w, acc[i][3]);
                }
            }
            __syncwarp();
            if (lane == 0) mbar_arrive(sb + BAR_EMPTY + 8 * s);
            if (++s == STAGES) { s = 0; ph ^= 1; }
        } while (!(word & LAST_BIT));

        {
            const uint32_t tag = (word >> TAG_SHIFT) & 1;
            char* slot = reinterpret_cast<char*>(prm.scratch->part + (h * CPT + cin) * SLOT_WORDS);
            char* part_st = slot + (lane & 16) * 32 + j * 16 + (lane & 8);
            l_run += __shfl_xor_sync(0xffffffffu, l_run, 8);
            z_run += __shfl_xor_sync(0xffffffffu, z_run, 8);
            l_run += __shfl_xor_sync(0xffffffffu, l_run, 16);
            z_run += __shfl_xor_sync(0xffffffffu, z_run, 16);
            st_relaxed_b64(slot + r * 256 + QC * 4 + j * 8, __float_as_uint(m_run), tagged(l_run, tag));
            const bool od = (lane & 8) != 0;
#pragma unroll
            for (int i = 0; i < 3; i++) {
                float k[4];
#pragma unroll
                for (int c = 0; c < 4; c++) k[c] = acc[i][c] + __shfl_xor_sync(0xffffffffu, acc[i + 3][c], 16);
                const float z0 = (od ? k[2] : k[0]) + __shfl_xor_sync(0xffffffffu, od ? k[0] : k[2], 8);
                const float z1 = (od ? k[3] : k[1]) + __shfl_xor_sync(0xffffffffu, od ? k[1] : k[3], 8);
                st_relaxed_b64(part_st + i * 128 + (i == 2 ? 64 : i == 1 ? (j & 4) * 16 : 0),
                               __float_as_uint(z0 - z_run), tagged(z1 - z_run, tag));
            }
            if (lane < QUARTERS) mbox_post(prm.scratch->mbox + (h * QUARTERS + lane) * MBOX_STRIDE, 1u);
        }

        if (cw >= RSLOTS * 12 / 32) return;
        const int ft = threadIdx.x - W_CONS * 32;
        const int rs = ft / 12;
        constexpr int RPT = P_ROWS / RSLOTS;
        float a0 = 0.f, a1 = 0.f, a2 = 0.f, a3 = 0.f;
        mbar_wait(sb + BAR_W, 0);
        const uint32_t ra = sb + OFF_RV + rs * (RSTRIDE * 4 - QC * 4) + ft * 16;
        uint32_t va = sb + piece_off(0) + ft * 16, step = KV_BYTES;
#pragma unroll 1
        for (int p = 0; p < NP; p++) {
            float w[RPT];
#pragma unroll
            for (int i = 0; i < RPT; i += 4) {
                const int4 w4 = lds128(sb + OFF_W + p * (P_ROWS * 4) + (rs * RPT + i) * 4);
                w[i] = __int_as_float(w4.x); w[i + 1] = __int_as_float(w4.y);
                w[i + 2] = __int_as_float(w4.z); w[i + 3] = __int_as_float(w4.w);
            }
            mbar_wait(sb + BAR_FIN + 8 * p, 0);
#pragma unroll
            for (int i = 0; i < RPT; i++) {
                const int4 v = lds128(va + i * (RSLOTS * QC * 4));
                a0 = fmaf(w[i], (float)v.x, a0);
                a1 = fmaf(w[i], (float)v.y, a1);
                a2 = fmaf(w[i], (float)v.z, a2);
                a3 = fmaf(w[i], (float)v.w, a3);
            }
            va += step;
            step = STAGE_BYTES - step;
        }
        sts128f(ra, a0, a1, a2, a3);
        asm volatile("bar.arrive 3, %0;" ::"n"(RSLOTS * 12 + 32) : "memory");
        return;
    }

    if (warp >= W_GATHER) {
        asm volatile("bar.sync 0, %0;" ::"n"(THREADS) : "memory");
        const int sub = lane >= 13, quad = min(lane - sub * 13, 12);
        const int sg = 2 * (warp - W_GATHER) + sub;
        const float* src = prm.scratch->part + ((h0 + cin / QUARTERS) * CPT + sg) * SLOT_WORDS +
                           (cin % QUARTERS) * 64 + quad * 4;
        uint4 dt[NSL];
        mbar_wait(sb + BAR_INIT, 0);
        const uint32_t tag = lds32(sb + OFF_TAG);
        mbar_wait(sb + BAR_G, 0);
        int spin = 0;
        uint32_t bad;
#pragma unroll 1
        do {
            static_for<NSL>([&](auto bc) {
                constexpr int b = decltype(bc)::value;
                dt[b] = ld_relaxed_2xb64<b * SG * SLOT_WORDS * 4>(src);
            });
            bad = 0;
#pragma unroll
            for (int b = 0; b < NSL; b++) bad |= (dt[b].y ^ tag) | (dt[b].w ^ tag);
        } while (__any_sync(0xffffffffu, bad & 1u) && ++spin < (1 << 20));
        float mh[NSL], m = -INFINITY;
#pragma unroll
        for (int b = 0; b < NSL; b++) {
            mh[b] = __shfl_sync(0xffffffffu, __uint_as_float(dt[b].x), sub * 13 + 12);
            m = fmaxf(m, mh[b]);
        }
        float a0 = 0.f, a1 = 0.f, a2 = 0.f, a3 = 0.f;
#pragma unroll
        for (int b = 0; b < NSL; b++) {
            const float w = ex2(mh[b] - m);
            a0 = fmaf(w, __uint_as_float(dt[b].x), a0);
            a1 = fmaf(w, __uint_as_float(dt[b].y), a1);
            a2 = fmaf(w, __uint_as_float(dt[b].z), a2);
            a3 = fmaf(w, __uint_as_float(dt[b].w), a3);
        }
        if (lane < 26) sts128f(sb + OFF_RG + sg * (RSTRIDE * 4) + quad * 16, quad == 12 ? m : a0, a1, a2, a3);
        asm volatile("bar.arrive 2, %0;" ::"n"(GW * 32 + 32) : "memory");
        return;
    }

    if (warp == W_FIN) {
        if (elect_one()) {
            prefetch_map(&maps.ks);
            prefetch_map(&maps.kz);
            prefetch_map(&maps.vs);
            prefetch_map(&maps.vz);
            prefetch_map(&maps.k);
            prefetch_map(&maps.v);
        }
        asm volatile("bar.sync 0, %0;" ::"n"(THREADS) : "memory");
        const char* lptr = reinterpret_cast<const char*>(prm.scratch->logit + (h0 + cin / QUARTERS) * F_ROWS) + lane * 16;
        __nv_bfloat16* optr = prm.out + h0 * D + cin * QC + 2 * lane;
        mbar_wait(sb + BAR_INIT, 0);
        const uint32_t tag = lds32(sb + OFF_TAG);
        uint4 rec[NP];
        bool ok;
        int spin = 0;
        do {
            static_for<NP>([&](auto ic) { rec[decltype(ic)::value] = ld_relaxed_2xb64<decltype(ic)::value * 512>(lptr); });
            uint32_t bad = 0;
#pragma unroll
            for (int i = 0; i < NP; i++) bad |= (rec[i].y ^ tag) | (rec[i].w ^ tag);
            ok = (bad & 1u) == 0;
        } while (!__all_sync(0xffffffffu, ok) && ++spin < (1 << 20));
        float mF = -INFINITY, lF = 0.f, zF = 0.f;
#pragma unroll
        for (int i = 0; i < NP; i++) mF = fmaxf(mF, fmaxf(__uint_as_float(rec[i].y), __uint_as_float(rec[i].w)));
        mF = warp_max(mF);
        const uint32_t wa = sb + OFF_W + (2 * lane % RSLOTS) * (P_ROWS / RSLOTS * 4) + (2 * lane / RSLOTS) * 4;
#pragma unroll
        for (int i = 0; i < NP; i++) {
            const float p0 = ex2(__uint_as_float(rec[i].y) - mF), p1 = ex2(__uint_as_float(rec[i].w) - mF);
            const float a0 = p0 * bf_lo(rec[i].x), a1 = p1 * bf_lo(rec[i].z);
            lF += p0 + p1;
            zF = fmaf(a0, bf_hi(rec[i].x), fmaf(a1, bf_hi(rec[i].z), zF));
            sts32(wa + i * (P_ROWS * 4), __float_as_uint(a0));
            sts32(wa + i * (P_ROWS * 4) + P_ROWS / RSLOTS * 4, __float_as_uint(a1));
        }
        __syncwarp();
        if (lane == 0) mbar_arrive(sb + BAR_W);
#pragma unroll
        for (int o = 16; o > 0; o >>= 1) {
            lF += __shfl_xor_sync(0xffffffffu, lF, o);
            zF += __shfl_xor_sync(0xffffffffu, zF, o);
        }
        mbar_wait(sb + BAR_END, 0);
        if (lane == 0) {
            unsigned int* box = prm.scratch->mbox + (h0 * QUARTERS + cin) * MBOX_STRIDE;
            int seen = 0;
            do seen += mbox_take(box); while (seen < CPT && ++spin < (1 << 20));
            mbar_arrive(sb + BAR_G);
        }
        __syncwarp();
        const uint32_t col = sb + (uint32_t)min(lane, QC / 2 - 1) * 8;
        asm volatile("bar.sync 2, %0;" ::"r"(__float_as_uint(lF + zF) == 0xffffffffu ? 32 : GW * 32 + 32) : "memory");
        float2 ml[SG], ga[SG];
#pragma unroll
        for (int g = 0; g < SG; g++) {
            ml[g] = lds64f(sb + OFF_RG + g * (RSTRIDE * 4) + QC * 4);
            ga[g] = lds64f(col + OFF_RG + g * (RSTRIDE * 4));
        }
        float M = mF;
#pragma unroll
        for (int g = 0; g < SG; g++) M = fmaxf(M, ml[g].x);
        float wF = ex2(mF - M);
        float L = wF * lF, b0 = -wF * zF, b1 = b0;
#pragma unroll
        for (int g = 0; g < SG; g++) {
            const float w = ex2(ml[g].x - M);
            L = fmaf(w, ml[g].y, L);
            b0 = fmaf(w, ga[g].x, b0);
            b1 = fmaf(w, ga[g].y, b1);
        }
        const float inv = __fdividef(1.f, L);
        wF *= inv;
        b0 *= inv;
        b1 *= inv;
        asm volatile("bar.sync 3, %0;"
                     ::"r"(__any_sync(0xffffffffu, __float_as_uint(wF + b0 + b1) == 0xffffffffu) ? 32 : RSLOTS * 12 + 32) : "memory");
        float2 rv[RSLOTS];
#pragma unroll
        for (int g = 0; g < RSLOTS; g++) rv[g] = lds64f(col + OFF_RV + g * (RSTRIDE * 4));
        static_for<3>([&](auto lc) {
            constexpr int o = RSLOTS / 2 >> decltype(lc)::value;
#pragma unroll
            for (int g = 0; g < o; g++) {
                rv[g].x += rv[g + o].x;
                rv[g].y += rv[g + o].y;
            }
        });
        if (lane < QC / 2)
            *reinterpret_cast<__nv_bfloat162*>(optr) = __floats2bfloat162_rn(fmaf(wF, rv[0].x, b0), fmaf(wF, rv[0].y, b1));
        return;
    }

    __syncwarp();
    asm volatile("bar.arrive 0, %0;" ::"n"(THREADS) : "memory");
    if (!elect_one()) return;
    const uint64_t pol = evict_first_policy();
    unsigned long long* ctr = prm.scratch->ctr;
    constexpr int total = TICKETS - (STAGES - 1) * CPT;
    const unsigned long long inc = 1ull << (15 * team);
    unsigned long long ticket = draw(ctr, inc);
    const uint32_t t_begin = now_ns();
    uint32_t w1 = 0, w2 = 0, w3 = 0;
    auto push = [&](uint32_t w) { w3 = w2; w2 = w1; w1 = w; };
    int s = 0, u = cin, k = 0, halves = 0, drawn = 0;
    uint32_t ph = 0;
    uint32_t t_draw = 0;
    bool init_done = false;
#pragma unroll 1
    for (;; k++) {
        const bool half = u >= UA;
        const int pos = half ? (u + UA) * (T / 2) : u * T;
        const int p8 = pos & ~7;
        const uint32_t fb = sb + BAR_FULLK + 8 * s;
        const uint32_t fv = sb + BAR_FULLV + 8 * s;
        const uint32_t dst = buf0 + s * STAGE_BYTES;
        halves += half;
        const bool gated = k >= STAGES && halves < STAGES;
        mbar_wait(sb + BAR_EMPTY + 8 * s, ph ^ 1);
        if (gated) mbar_wait(w3 & ~1u, w3 & 1u);
        if (k > 0) tma3d(dst + OFF_K, half ? &maps.kh : &maps.k, 0, pos, h0, fb, pol);
        bulk_load(dst + OFF_COS, prm.k_cos + (size_t)pos * D, half ? CS_BYTES / 2 : CS_BYTES, fb);
        bulk_load(dst + OFF_SIN, prm.k_sin + (size_t)pos * D, half ? CS_BYTES / 2 : CS_BYTES, fb);
        tma2d(dst + OFF_KS, &maps.ks, p8, h0, fb);
        tma2d(dst + OFF_KZ, &maps.kz, p8, h0, fb);
        tma2d(dst + OFF_VS, &maps.vs, p8, h0, fb);
        tma2d(dst + OFF_VZ, &maps.vz, p8, h0, fb);
        if (k >= STAGES) ticket = draw(ctr, inc);
        if ((u & (TEAMS - 1)) == team && !half) {
            l2_prefetch(prm.k_cos + (size_t)(pos + CS_AHEAD * T) * D, CS_BYTES);
            l2_prefetch(prm.k_sin + (size_t)(pos + CS_AHEAD * T) * D, CS_BYTES);
        }
        if (half) t_draw = now_ns();
        push(fb | ph);
        if ((unsigned)(pos - F0) < (unsigned)F_ROWS) {
            mbar_arrive(fv);
            prefetch_map(&maps.kh);
            prefetch_map(&maps.vh);
            prefetch_map(&maps.vf);
        } else {
            if (gated) mbar_wait(w3 & ~1u, w3 & 1u);
            mbar_expect_tx(fv, half ? KV_BYTES / 2 : KV_BYTES);
            tma3d(dst + OFF_V, half ? &maps.vh : &maps.v, 0, pos, h0, fv, pol);
            push(fv | ph);
        }
        int un = u + CPT;
        uint32_t tag = 0;
        if (k >= STAGES - 1) {
            uint32_t lo, hi;
            asm volatile("st.shared.b64 [%2], %3;\nld.volatile.shared.v2.u32 {%0,%1}, [%2];"
                         : "=r"(lo), "=r"(hi) : "r"(sb + OFF_TICKET), "l"(ticket) : "memory");
            const int t01 = (int)(lo & 0x3fffffff), t23 = (int)(__funnelshift_r(lo, hi, 30) & 0x3fffffff);
            const int t = ((team & 2 ? t23 : t01) >> (15 * (team & 1))) & 0x7fff;
            drawn = (t01 & 0x7fff) + (t01 >> 15) + (t23 & 0x7fff) + (t23 >> 15);
            tag = ~hi >> 31;
            un = STAGES * CPT + t;
        }
        const bool start_fin = !init_done && un >= TICKETS - 2 * CPT;
        init_done |= start_fin;
        sts32(sb + OFF_UIDX + 4 * s, pos | (tag << TAG_SHIFT) | (un >= TICKETS ? LAST_BIT : 0));
        mbar_expect_tx(fb, half ? KSIDE_BYTES - KV_BYTES / 2 - CS_BYTES : KSIDE_BYTES);
        if (start_fin) {
            sts32(sb + OFF_TAG, tag);
            mbar_arrive(sb + BAR_INIT);
        }
        if (un >= TICKETS) break;
        u = un;
        if (++s == STAGES) { s = 0; ph ^= 1; }
    }
    mbar_arrive(sb + BAR_END);
    if (drawn == TEAMS * total - 1) draw(ctr, (1ull << 63) - total * 0x0000200040008001ull);
    uint32_t t_next = now_ns();
    int dt = (int)(t_draw - t_next) +
             (int)(((t_draw - t_begin) >> 4) * (uint32_t)(PACE_BASE + min(TEAMS * total - drawn, 512)) / (PACE_DIV / 16));
    dt = max(dt, 0) / NP;
    if (halves < STAGES) {
        mbar_wait(sb + BAR_EMPTY + 8 * s, ph);
        dt = 0;
    }
#pragma unroll 1
    for (int p = 0; p < NP; p++) {
        const uint32_t fb = sb + BAR_FIN + 8 * p;
        t_next += dt;
        while ((int)(now_ns() - t_next) < 0 && !mbar_test(w2 & ~1u, w2 & 1u)) {}
        mbar_expect_tx(fb, PIECE_BYTES);
        tma3d(sb + piece_off(p), &maps.vf, (cin % QUARTERS) * QC, F0 + p * P_ROWS, h0 + cin / QUARTERS, fb, pol);
        push(fb);
    }
}

__global__ void __launch_bounds__(128)
fallback_partial_kernel(const Params prm, const int* qv, const __nv_bfloat16* ks, const __nv_bfloat16* kz,
                        const __nv_bfloat16* vs, const __nv_bfloat16* vz) {
    const int h = blockIdx.y, slot = blockIdx.x * 4 + (threadIdx.x >> 5), lane = threadIdx.x & 31;
    float qa[3], qb[3], acc[6] = {0.f, 0.f, 0.f, 0.f, 0.f, 0.f};
    for (int i = 0; i < 3; i++) {
        const int d = 32 * i + lane;
        const __nv_bfloat16 x1 = prm.q[h * D + d], x2 = prm.q[h * D + d + HALF];
        qa[i] = __bfloat162float(__hsub_rn(__hmul_rn(x1, prm.q_cos[d]), __hmul_rn(x2, prm.q_sin[d])));
        qb[i] = __bfloat162float(__hadd_rn(__hmul_rn(x2, prm.q_cos[d + HALF]), __hmul_rn(x1, prm.q_sin[d + HALF])));
    }
    float m = -3e38f, l = 0.f;
    for (int pos = slot; pos < S; pos += CPT) {
        const size_t row = (size_t)h * S + pos;
        const float z = __bfloat162float(kz[row]);
        float dot = 0.f;
        for (int i = 0; i < 3; i++) {
            const int d = 32 * i + lane;
            const float a = (float)prm.qk[row * D + d] - z, b = (float)prm.qk[row * D + d + HALF] - z;
            const __nv_bfloat16* c = prm.k_cos + pos * D + d;
            const __nv_bfloat16* sn = prm.k_sin + pos * D + d;
            dot += qa[i] * (a * __bfloat162float(c[0]) - b * __bfloat162float(sn[0])) +
                   qb[i] * (b * __bfloat162float(c[HALF]) + a * __bfloat162float(sn[HALF]));
        }
        for (int o = 16; o > 0; o >>= 1) dot += __shfl_xor_sync(0xffffffffu, dot, o);
        const float sv = dot * __bfloat162float(ks[row]) * QK_SCALE;
        const float m_new = fmaxf(m, sv), alpha = ex2(m - m_new), p = ex2(sv - m_new);
        const float pv = p * __bfloat162float(vs[row]), zv = __bfloat162float(vz[row]);
        m = m_new;
        l = l * alpha + p;
        for (int i = 0; i < 6; i++) acc[i] = acc[i] * alpha + pv * ((float)qv[row * D + 32 * i + lane] - zv);
    }
    float* dst = prm.scratch->part + (h * CPT + slot) * SLOT_WORDS;
    for (int i = 0; i < 6; i++) dst[32 * i + lane] = acc[i];
    if (lane == 0) {
        dst[D] = m;
        dst[D + 1] = l;
    }
}

__global__ void __launch_bounds__(D) fallback_merge_kernel(const Params prm) {
    const float* src = prm.scratch->part + blockIdx.x * CPT * SLOT_WORDS;
    float m = -3e38f, l = 0.f, o = 0.f;
    for (int c = 0; c < CPT; c++) m = fmaxf(m, src[c * SLOT_WORDS + D]);
    for (int c = 0; c < CPT; c++) {
        const float w = ex2(src[c * SLOT_WORDS + D] - m);
        l += w * src[c * SLOT_WORDS + D + 1];
        o += w * src[c * SLOT_WORDS + threadIdx.x];
    }
    prm.out[blockIdx.x * D + threadIdx.x] = __float2bfloat16_rn(o / l);
}

typedef CUresult (*EncodeTiledFn)(CUtensorMap*, CUtensorMapDataType, cuuint32_t, void*, const cuuint64_t*,
                                  const cuuint64_t*, const cuuint32_t*, const cuuint32_t*,
                                  CUtensorMapInterleave, CUtensorMapSwizzle, CUtensorMapL2promotion,
                                  CUtensorMapFloatOOBfill);

void make_kv_map(EncodeTiledFn enc, CUtensorMap* m, const void* ptr, int cols, int rows, int heads,
                 CUtensorMapL2promotion promo) {
    cuuint64_t dims[3] = {(cuuint64_t)D, (cuuint64_t)S, (cuuint64_t)H};
    cuuint64_t strides[2] = {(cuuint64_t)D * 4, (cuuint64_t)S * D * 4};
    cuuint32_t box[3] = {(cuuint32_t)cols, (cuuint32_t)rows, (cuuint32_t)heads};
    cuuint32_t es[3] = {1, 1, 1};
    enc(m, CU_TENSOR_MAP_DATA_TYPE_INT32, 3, const_cast<void*>(ptr), dims, strides, box, es,
        CU_TENSOR_MAP_INTERLEAVE_NONE, CU_TENSOR_MAP_SWIZZLE_NONE, promo, CU_TENSOR_MAP_FLOAT_OOB_FILL_NONE);
}

void make_scale_map(EncodeTiledFn enc, CUtensorMap* m, const void* ptr) {
    cuuint64_t dims[2] = {(cuuint64_t)S, (cuuint64_t)H};
    cuuint64_t strides[1] = {(cuuint64_t)S * 2};
    cuuint32_t box[2] = {8, (cuuint32_t)G};
    cuuint32_t es[2] = {1, 1};
    enc(m, CU_TENSOR_MAP_DATA_TYPE_BFLOAT16, 2, const_cast<void*>(ptr), dims, strides, box, es,
        CU_TENSOR_MAP_INTERLEAVE_NONE, CU_TENSOR_MAP_SWIZZLE_NONE, CU_TENSOR_MAP_L2_PROMOTION_L2_256B,
        CU_TENSOR_MAP_FLOAT_OOB_FILL_NONE);
}

}

extern "C" void kernel_launch(void* const* d_in, const int* in_sizes, int n_in, void* d_out, int out_size) {
    (void)in_sizes; (void)n_in; (void)out_size;
    static EncodeTiledFn enc = nullptr;
    static Scratch* scratch = nullptr;
    static int sms = 0;
    if (!enc) {
        void* fn = nullptr;
        cudaDriverEntryPointQueryResult qr;
        cudaGetDriverEntryPoint("cuTensorMapEncodeTiled", &fn, cudaEnableDefault, &qr);
        enc = (EncodeTiledFn)fn;
        int dev = 0;
        cudaGetDevice(&dev);
        cudaDeviceGetAttribute(&sms, cudaDevAttrMultiProcessorCount, dev);
        cudaGetSymbolAddress((void**)&scratch, g_scratch);
        cudaFuncSetAttribute(kv_decode_kernel, cudaFuncAttributeMaxDynamicSharedMemorySize, SMEM_BYTES);
    }
    Params prm;
    prm.q = (const __nv_bfloat16*)d_in[0];
    prm.qk = (const int*)d_in[1];
    prm.q_cos = (const __nv_bfloat16*)d_in[7];
    prm.q_sin = (const __nv_bfloat16*)d_in[8];
    prm.k_cos = (const __nv_bfloat16*)d_in[9];
    prm.k_sin = (const __nv_bfloat16*)d_in[10];
    prm.out = (__nv_bfloat16*)d_out;
    prm.scratch = scratch;
    if (sms < TEAMS * CPT) {
        fallback_partial_kernel<<<dim3(CPT / 4, H), 128>>>(
            prm, (const int*)d_in[4], (const __nv_bfloat16*)d_in[2], (const __nv_bfloat16*)d_in[3],
            (const __nv_bfloat16*)d_in[5], (const __nv_bfloat16*)d_in[6]);
        fallback_merge_kernel<<<H, D>>>(prm);
        return;
    }
    Maps maps;
    make_kv_map(enc, &maps.k, prm.qk, D, T, G, CU_TENSOR_MAP_L2_PROMOTION_L2_128B);
    make_kv_map(enc, &maps.v, d_in[4], D, T, G, CU_TENSOR_MAP_L2_PROMOTION_L2_128B);
    make_kv_map(enc, &maps.kh, prm.qk, D, T / 2, G, CU_TENSOR_MAP_L2_PROMOTION_L2_128B);
    make_kv_map(enc, &maps.vh, d_in[4], D, T / 2, G, CU_TENSOR_MAP_L2_PROMOTION_L2_128B);
    make_kv_map(enc, &maps.vf, d_in[4], QC, P_ROWS, 1, CU_TENSOR_MAP_L2_PROMOTION_NONE);
    make_scale_map(enc, &maps.ks, d_in[2]);
    make_scale_map(enc, &maps.kz, d_in[3]);
    make_scale_map(enc, &maps.vs, d_in[5]);
    make_scale_map(enc, &maps.vz, d_in[6]);

    kv_decode_kernel<<<TEAMS * CPT, THREADS, SMEM_BYTES>>>(prm, maps);
}
```

```cpp
#include <cuda_runtime.h>
#include <cuda_bf16.h>
#include <cuda.h>
#include <stdint.h>
#include <type_traits>

namespace {

constexpr int H = 32;
constexpr int S = 16384;
constexpr int D = 192;
constexpr int HALF = D / 2;
constexpr float QK_SCALE = 0.07216878364870322f * 1.4426950408889634f;

constexpr int G = 8;
constexpr int T = 4;
constexpr int TEAMS = H / G;
constexpr int UNITS = S / T;
constexpr int STAGES = 3;
constexpr int TAIL_UNITS = 130;
constexpr int UA = UNITS - TAIL_UNITS;
constexpr int TICKETS = UA + 2 * TAIL_UNITS;
constexpr int CS_AHEAD = TAIL_UNITS;
constexpr int F_ROWS = 512;
constexpr int P_ROWS = 64;
constexpr int NP = F_ROWS / P_ROWS;
constexpr int F0 = UA * T - F_ROWS;
constexpr int QUARTERS = 4;
constexpr int QC = D / QUARTERS;
constexpr int CPT = G * QUARTERS;
constexpr int GW = 4;
constexpr int SG = 2 * GW;
constexpr int NSL = CPT / SG;
constexpr int RSLOTS = 8;
constexpr int RSTRIDE = 52;
constexpr int SLOT_WORDS = QUARTERS * 64;

constexpr int MBOX_STRIDE = 32;
constexpr int PACE_BASE = 280;
constexpr int PACE_DIV = 20700;

constexpr int W_FIN = 1;
constexpr int W_GATHER = 2;
constexpr int W_CONS = W_GATHER + GW;
constexpr int THREADS = (W_CONS + G) * 32;

constexpr int KV_BYTES = G * T * D * 4;
constexpr int ROWS_BYTES = T * D * 4;
constexpr int CS_BYTES = T * D * 2;
constexpr int SC_BYTES = G * 8 * 2;
constexpr int OFF_K = 0;
constexpr int OFF_V = KV_BYTES;
constexpr int OFF_COS = 2 * KV_BYTES;
constexpr int OFF_SIN = OFF_COS + CS_BYTES;
constexpr int OFF_KS = OFF_SIN + CS_BYTES;
constexpr int OFF_KZ = OFF_KS + SC_BYTES;
constexpr int OFF_VS = OFF_KZ + SC_BYTES;
constexpr int OFF_VZ = OFF_VS + SC_BYTES;
constexpr int STAGE_BYTES = OFF_VZ + SC_BYTES;
constexpr int KSIDE_BYTES = STAGE_BYTES - KV_BYTES;
constexpr int PIECE_BYTES = P_ROWS * QC * 4;

constexpr int BAR_FULLK = 0;
constexpr int BAR_FULLV = 8 * STAGES;
constexpr int BAR_EMPTY = 16 * STAGES;
constexpr int BAR_INIT = 24 * STAGES;
constexpr int BAR_END = BAR_INIT + 8;
constexpr int BAR_W = BAR_END + 8;
constexpr int BAR_G = BAR_W + 8;
constexpr int BAR_FIN = BAR_G + 8;
constexpr int OFF_UIDX = 224;
constexpr int OFF_TAG = OFF_UIDX + 4 * STAGES;
constexpr int OFF_TICKET = OFF_TAG + 4;
constexpr int LAST_BIT = 1 << 30;
constexpr int TAG_SHIFT = 29;
constexpr int POS_MASK = (1 << TAG_SHIFT) - 1;
constexpr int CTRL_BYTES = 256;
constexpr int OFF_W = CTRL_BYTES + STAGES * STAGE_BYTES;
constexpr int OFF_RV = OFF_W + F_ROWS * 4;
constexpr int OFF_RG = OFF_RV + RSLOTS * RSTRIDE * 4;
constexpr int SMEM_USED = OFF_W + 2 * KV_BYTES;
static_assert(OFF_RG + SG * RSTRIDE * 4 <= OFF_W + KV_BYTES / 2 && NP <= 2 * STAGES + 2, "final-phase buffers");
static_assert(BAR_FIN + 8 * NP <= OFF_UIDX && OFF_TICKET % 8 == 0, "control block");
constexpr int SMEM_BYTES = SMEM_USED;
static_assert(STAGE_BYTES % 128 == 0 && PIECE_BYTES % 128 == 0 && TEAMS == T, "layout");
static_assert(SMEM_BYTES <= 232448, "shared memory budget");

struct __align__(128) Scratch {
    float part[H * CPT * SLOT_WORDS];
    uint2 logit[H * F_ROWS];
    unsigned int mbox[H * QUARTERS * MBOX_STRIDE];
    unsigned long long ctr[16];
};
__device__ Scratch g_scratch;

__device__ __forceinline__ uint32_t smem_u32(const void* p) {
    return (uint32_t)__cvta_generic_to_shared(p);
}
__device__ __forceinline__ void mbar_init(uint32_t bar, int cnt) {
    asm volatile("mbarrier.init.shared::cta.b64 [%0], %1;" ::"r"(bar), "r"(cnt) : "memory");
}
__device__ __forceinline__ void mbar_expect_tx(uint32_t bar, uint32_t bytes) {
    asm volatile("mbarrier.arrive.expect_tx.shared::cta.b64 _, [%0], %1;" ::"r"(bar), "r"(bytes) : "memory");
}
__device__ __forceinline__ void mbar_arrive(uint32_t bar) {
    asm volatile("mbarrier.arrive.shared::cta.b64 _, [%0];" ::"r"(bar) : "memory");
}
__device__ __forceinline__ void mbar_wait(uint32_t bar, uint32_t parity) {
    asm volatile(
        "{\n"
        ".reg .pred p;\n"
        ".reg .u32 n;\n"
        "mov.u32 n, 0;\n"
        "WAIT_%=:\n"
        "mbarrier.try_wait.parity.shared::cta.b64 p, [%0], %1;\n"
        "@p bra DONE_%=;\n"
        "add.u32 n, n, 1;\n"
        "setp.lt.u32 p, n, 0x400000;\n"
        "@p bra WAIT_%=;\n"
        "DONE_%=:\n"
        "}" ::"r"(bar), "r"(parity) : "memory");
}
__device__ __forceinline__ bool mbar_test(uint32_t bar, uint32_t parity) {
    uint32_t ok;
    asm volatile("{\n.reg .pred p;\nmbarrier.test_wait.parity.shared::cta.b64 p, [%1], %2;\nselp.u32 %0, 1, 0, p;\n}"
                 : "=r"(ok) : "r"(bar), "r"(parity) : "memory");
    return ok != 0;
}
__device__ __forceinline__ uint32_t now() {
    uint32_t t;
    asm volatile("mov.u32 %0, %%clock;" : "=r"(t)::"memory");
    return t;
}
__device__ __forceinline__ bool elect_one() {
    uint32_t p;
    asm volatile("{\n.reg .pred p;\nelect.sync _|p, 0xffffffff;\nselp.u32 %0, 1, 0, p;\n}" : "=r"(p));
    return p != 0;
}
__device__ __forceinline__ void bulk_load(uint32_t dst, const void* src, uint32_t bytes, uint32_t bar) {
    asm volatile("cp.async.bulk.shared::cluster.global.mbarrier::complete_tx::bytes [%0], [%1], %2, [%3];"
                 ::"r"(dst), "l"(src), "r"(bytes), "r"(bar) : "memory");
}
__device__ __forceinline__ void tma3d(uint32_t dst, const CUtensorMap* map, int c0, int c1, int c2,
                                      uint32_t bar, uint64_t pol) {
    asm volatile(
        "cp.async.bulk.tensor.3d.shared::cluster.global.mbarrier::complete_tx::bytes.L2::cache_hint"
        " [%0], [%1, {%2, %3, %4}], [%5], %6;"
        ::"r"(dst), "l"(map), "r"(c0), "r"(c1), "r"(c2), "r"(bar), "l"(pol) : "memory");
}
__device__ __forceinline__ void tma2d(uint32_t dst, const CUtensorMap* map, int c0, int c1, uint32_t bar) {
    asm volatile(
        "cp.async.bulk.tensor.2d.shared::cluster.global.mbarrier::complete_tx::bytes"
        " [%0], [%1, {%2, %3}], [%4];"
        ::"r"(dst), "l"(map), "r"(c0), "r"(c1), "r"(bar) : "memory");
}
__device__ __forceinline__ void l2_prefetch(const void* src, uint32_t bytes) {
    asm volatile("cp.async.bulk.prefetch.L2.global [%0], %1;" ::"l"(src), "r"(bytes) : "memory");
}
__device__ __forceinline__ void prefetch_map(const CUtensorMap* map) {
    asm volatile("prefetch.tensormap [%0];" ::"l"(map) : "memory");
}
__device__ __forceinline__ uint64_t evict_first_policy() {
    uint64_t pol;
    asm volatile("createpolicy.fractional.L2::evict_first.b64 %0, 1.0;" : "=l"(pol));
    return pol;
}
__device__ __forceinline__ float ex2(float x) {
    float y;
    asm("ex2.approx.ftz.f32 %0, %1;" : "=f"(y) : "f"(x));
    return y;
}
__device__ __forceinline__ float bf_lo(uint32_t x) { return __uint_as_float(x << 16); }
__device__ __forceinline__ float bf_hi(uint32_t x) { return __uint_as_float(x & 0xffff0000u); }
__device__ __forceinline__ uint32_t bf2_mul(uint32_t a, uint32_t b) {
    uint32_t d;
    asm("mul.rn.bf16x2 %0, %1, %2;" : "=r"(d) : "r"(a), "r"(b));
    return d;
}
__device__ __forceinline__ uint32_t bf2_add(uint32_t a, uint32_t b) {
    uint32_t d;
    asm("add.rn.bf16x2 %0, %1, %2;" : "=r"(d) : "r"(a), "r"(b));
    return d;
}
__device__ __forceinline__ uint32_t bf2_sub(uint32_t a, uint32_t b) {
    uint32_t d;
    asm("sub.rn.bf16x2 %0, %1, %2;" : "=r"(d) : "r"(a), "r"(b));
    return d;
}
__device__ __forceinline__ float lds_bf16(uint32_t addr) {
    unsigned short v;
    asm volatile("ld.shared.u16 %0, [%1];" : "=h"(v) : "r"(addr));
    return __uint_as_float(((uint32_t)v) << 16);
}
__device__ __forceinline__ int4 lds128(uint32_t addr) {
    int4 v;
    asm volatile("ld.shared.v4.s32 {%0,%1,%2,%3}, [%4];" : "=r"(v.x), "=r"(v.y), "=r"(v.z), "=r"(v.w) : "r"(addr));
    return v;
}
__device__ __forceinline__ uint2 lds64(uint32_t addr) {
    uint2 v;
    asm volatile("ld.shared.v2.u32 {%0,%1}, [%2];" : "=r"(v.x), "=r"(v.y) : "r"(addr));
    return v;
}
__device__ __forceinline__ float2 lds64f(uint32_t addr) {
    const uint2 v = lds64(addr);
    return make_float2(__uint_as_float(v.x), __uint_as_float(v.y));
}
__device__ __forceinline__ uint32_t lds32(uint32_t addr) {
    uint32_t v;
    asm volatile("ld.shared.u32 %0, [%1];" : "=r"(v) : "r"(addr) : "memory");
    return v;
}
__device__ __forceinline__ void sts32(uint32_t addr, uint32_t v) {
    asm volatile("st.shared.u32 [%0], %1;" ::"r"(addr), "r"(v) : "memory");
}
__device__ __forceinline__ void sts128f(uint32_t addr, float a, float b, float c, float d) {
    asm volatile("st.shared.v4.f32 [%0], {%1,%2,%3,%4};" ::"r"(addr), "f"(a), "f"(b), "f"(c), "f"(d) : "memory");
}
__device__ __forceinline__ float warp_max(float x) {
    int k = __float_as_int(x);
    k ^= (k >> 31) & 0x7fffffff;
    k = __reduce_max_sync(0xffffffffu, k);
    return __int_as_float(k ^ ((k >> 31) & 0x7fffffff));
}

__device__ __forceinline__ uint32_t tagged(float x, uint32_t tag) { return (__float_as_uint(x) & ~1u) | tag; }

__device__ __forceinline__ void st_relaxed_b64(const void* p, uint32_t lo, uint32_t hi) {
    asm volatile("{\n.reg .b64 v;\nmov.b64 v, {%1,%2};\nst.relaxed.gpu.global.b64 [%0], v;\n}"
                 ::"l"(p), "r"(lo), "r"(hi) : "memory");
}
template <int OFF>
__device__ __forceinline__ uint4 ld_relaxed_2xb64(const void* base) {
    uint4 v;
    asm volatile("{\n.reg .b64 a, b;\nld.relaxed.gpu.global.v2.b64 {a, b}, [%4+%5];\n"
                 "mov.b64 {%0,%1}, a;\nmov.b64 {%2,%3}, b;\n}"
                 : "=r"(v.x), "=r"(v.y), "=r"(v.z), "=r"(v.w) : "l"(base), "n"(OFF) : "memory");
    return v;
}
__device__ __forceinline__ void mbox_post(unsigned int* box, unsigned int bits) {
    asm volatile("red.relaxed.gpu.global.add.u32 [%0], %1;" ::"l"(box), "r"(bits) : "memory");
}
__device__ __forceinline__ unsigned int mbox_take(unsigned int* box) {
    unsigned int v;
    asm volatile("atom.relaxed.gpu.global.exch.b32 %0, [%1], 0;" : "=r"(v) : "l"(box) : "memory");
    return v;
}
template <int OFF>
__device__ __forceinline__ uint2 ldg64(const void* base) {
    uint2 v;
    asm volatile("ld.global.nc.v2.u32 {%0,%1}, [%2+%3];" : "=r"(v.x), "=r"(v.y) : "l"(base), "n"(OFF));
    return v;
}
template <int N, typename F>
__device__ __forceinline__ void static_for(F&& f) {
    if constexpr (N > 0) {
        static_for<N - 1>(f);
        f(std::integral_constant<int, N - 1>{});
    }
}
__device__ __forceinline__ unsigned long long draw(unsigned long long* ctr, unsigned long long inc) {
    unsigned long long v;
    asm volatile("atom.relaxed.gpu.global.add.u64 %0, [%1], %2;" : "=l"(v) : "l"(ctr), "l"(inc) : "memory");
    return v;
}

__device__ __forceinline__ uint32_t piece_off(int p) {
    return CTRL_BYTES + KV_BYTES / 2 + (p >> 1) * STAGE_BYTES + (p & 1) * KV_BYTES;
}
static_assert(PIECE_BYTES == KV_BYTES / 2 && OFF_K == 0 && OFF_V == KV_BYTES, "piece placement");

struct Params {
    const int* qk;
    const __nv_bfloat16* k_cos;
    const __nv_bfloat16* k_sin;
    Scratch* scratch;
    const __nv_bfloat16* q;
    const __nv_bfloat16* q_cos;
    const __nv_bfloat16* q_sin;
    __nv_bfloat16* out;
};
struct Maps {
    CUtensorMap k, v, ks, kz, vs, vz, kh, vh, vf;
};

__global__ void __launch_bounds__(THREADS, 1)
kv_decode_kernel(const __grid_constant__ Params prm, const __grid_constant__ Maps maps) {
    extern __shared__ __align__(1024) unsigned char smem[];
    const uint32_t sb = __shfl_sync(0xffffffffu, smem_u32(smem), 0);
    if (threadIdx.x < 32 && elect_one()) {
        mbar_init(sb + BAR_FULLK, 1);
        asm volatile("fence.mbarrier_init.release.cluster;" ::: "memory");
        const uint32_t row = (blockIdx.x % TEAMS) * (G * S - 1) + blockIdx.x;
        const char* src = reinterpret_cast<const char*>(prm.qk) + row * (size_t)(D * 4);
        uint32_t dst = sb + CTRL_BYTES;
#pragma unroll 1
        do {
            bulk_load(dst, src, ROWS_BYTES, sb + BAR_FULLK);
            dst += ROWS_BYTES;
            src += S * D * 4;
        } while (dst != sb + CTRL_BYTES + KV_BYTES);
#pragma unroll
        for (int i = 1; i < BAR_FIN / 8 + NP; i++) mbar_init(sb + 8 * i, (unsigned)(i - BAR_EMPTY / 8) < STAGES ? G : 1);
        asm volatile("fence.mbarrier_init.release.cluster;" ::: "memory");
    }
    uint32_t bid;
    asm volatile("mov.u32 %0, %%ctaid.x;" : "=r"(bid));
    const int team = bid % TEAMS;
    const int cin = bid / TEAMS;
    const int h0 = team * G;
    const uint32_t buf0 = sb + CTRL_BYTES;
    const int warp = __shfl_sync(0xffffffffu, threadIdx.x >> 5, 0);
    const int lane = threadIdx.x & 31;

    if (warp >= W_CONS) {
        const int cw = warp - W_CONS;
        const int h = h0 + cw;
        const int r = lane >> 3;
        const int j = lane & 7;

        float qa[3][4], qb[3][4];
        {
            const __nv_bfloat16* qp = prm.q + h * D + 4 * j;
            const __nv_bfloat16* cp = prm.q_cos + 4 * j;
            const __nv_bfloat16* sp = prm.q_sin + 4 * j;
            static_for<3>([&](auto ic) {
                constexpr int i = decltype(ic)::value;
                const uint2 x1 = ldg64<64 * i>(qp), x2 = ldg64<64 * i + 2 * HALF>(qp);
                const uint2 c1 = ldg64<64 * i>(cp), c2 = ldg64<64 * i + 2 * HALF>(cp);
                const uint2 s1 = ldg64<64 * i>(sp), s2 = ldg64<64 * i + 2 * HALF>(sp);
                const uint32_t a0 = bf2_sub(bf2_mul(x1.x, c1.x), bf2_mul(x2.x, s1.x));
                const uint32_t a1 = bf2_sub(bf2_mul(x1.y, c1.y), bf2_mul(x2.y, s1.y));
                const uint32_t b0 = bf2_add(bf2_mul(x2.x, c2.x), bf2_mul(x1.x, s2.x));
                const uint32_t b1 = bf2_add(bf2_mul(x2.y, c2.y), bf2_mul(x1.y, s2.y));
                qa[i][0] = bf_lo(a0); qa[i][1] = bf_hi(a0); qa[i][2] = bf_lo(a1); qa[i][3] = bf_hi(a1);
                qb[i][0] = bf_lo(b0); qb[i][1] = bf_hi(b0); qb[i][2] = bf_lo(b1); qb[i][3] = bf_hi(b1);
            });
        }
        float acc[6][4];
#pragma unroll
        for (int i = 0; i < 6; i++)
#pragma unroll
            for (int c = 0; c < 4; c++) acc[i][c] = 0.f;
        float m_run = -3e38f, l_run = 0.f;
        float z_run = 0.f;

        const uint32_t va_off = OFF_V + ((lane & 16) ? 384 : 0);
        const uint32_t vb_off = OFF_V + ((lane & 16) ? 0 : 384);
        uint32_t kv_off = (uint32_t)((cw * T + r) * (D * 4) + j * 16);
        uint32_t cs_off = (uint32_t)(OFF_COS + r * (D * 2) + j * 8);
        uint32_t sc_off = (uint32_t)(OFF_KS + cw * 16 + r * 2);
        float mask = 0.f;

        asm volatile("bar.sync 0, %0;" ::"n"(THREADS) : "memory");

        int s = 0, word;
        uint32_t ph = 0;
#pragma unroll 1
        do {
            mbar_wait(sb + BAR_FULLK + 8 * s, ph);
            word = (int)lds32(sb + OFF_UIDX + 4 * s);
            const int pos = word & POS_MASK;
            if (pos >= UA * T) {
                kv_off = (uint32_t)((cw * (T / 2) + (r & 1)) * (D * 4) + j * 16);
                cs_off = (uint32_t)(OFF_COS + (r & 1) * (D * 2) + j * 8);
                sc_off = (uint32_t)(OFF_KS + cw * 16 + (r & 1) * 2);
                mask = r >= 2 ? -INFINITY : 0.f;
            }
            const uint32_t st = buf0 + s * STAGE_BYTES;
            const uint32_t sc = st + sc_off + (pos & 7) * 2;
            const float kz = lds_bf16(sc + SC_BYTES);
            const float ks = lds_bf16(sc) * QK_SCALE;
            const float vs = lds_bf16(sc + 2 * SC_BYTES);
            const float vz = lds_bf16(sc + 3 * SC_BYTES);

            float d0 = 0.f, d1 = 0.f;
#pragma unroll
            for (int i = 0; i < 3; i++) {
                const int4 ka = lds128(st + kv_off + i * 128);
                const int4 kb = lds128(st + kv_off + (i + 3) * 128);
                const uint2 ca = lds64(st + cs_off + i * 64);
                const uint2 cb = lds64(st + cs_off + (i + 3) * 64);
                const uint2 sa = lds64(st + cs_off + CS_BYTES + i * 64);
                const uint2 sb2 = lds64(st + cs_off + CS_BYTES + (i + 3) * 64);
                const float a[4] = {(float)ka.x - kz, (float)ka.y - kz, (float)ka.z - kz, (float)ka.w - kz};
                const float b[4] = {(float)kb.x - kz, (float)kb.y - kz, (float)kb.z - kz, (float)kb.w - kz};
                const float fca[4] = {bf_lo(ca.x), bf_hi(ca.x), bf_lo(ca.y), bf_hi(ca.y)};
                const float fcb[4] = {bf_lo(cb.x), bf_hi(cb.x), bf_lo(cb.y), bf_hi(cb.y)};
                const float fsa[4] = {bf_lo(sa.x), bf_hi(sa.x), bf_lo(sa.y), bf_hi(sa.y)};
                const float fsb[4] = {bf_lo(sb2.x), bf_hi(sb2.x), bf_lo(sb2.y), bf_hi(sb2.y)};
#pragma unroll
                for (int c = 0; c < 4; c++) {
                    const float ra = fmaf(a[c], fca[c], -b[c] * fsa[c]);
                    const float rb = fmaf(b[c], fcb[c], a[c] * fsb[c]);
                    d0 = fmaf(qa[i][c], ra, d0);
                    d1 = fmaf(qb[i][c], rb, d1);
                }
            }
            float dot = d0 + d1;
            dot += __shfl_xor_sync(0xffffffffu, dot, 1);
            dot += __shfl_xor_sync(0xffffffffu, dot, 2);
            dot += __shfl_xor_sync(0xffffffffu, dot, 4);
            const float sv = dot * ks;

            if ((unsigned)(pos - F0) < (unsigned)F_ROWS) {
                if (j == 0)
                    st_relaxed_b64(prm.scratch->logit + h * F_ROWS + (pos - F0) + r,
                                   (__float_as_uint(vs) >> 16) | __float_as_uint(vz),
                                   tagged(fmaxf(sv, -3e38f), (word >> TAG_SHIFT) & 1));
            } else {
                if (__any_sync(0xffffffffu, sv > m_run)) {
                    float m_new = fmaxf(sv, __shfl_xor_sync(0xffffffffu, sv, 8));
                    m_new = fmaxf(m_run, fmaxf(m_new, __shfl_xor_sync(0xffffffffu, m_new, 16)));
                    const float alpha = ex2(m_run - m_new);
                    l_run *= alpha;
                    z_run *= alpha;
#pragma unroll
                    for (int i = 0; i < 6; i++)
#pragma unroll
                        for (int c = 0; c < 4; c++) acc[i][c] *= alpha;
                    m_run = m_new;
                }
                const float p = ex2(sv - m_run + mask);
                const float pv = p * vs;
                l_run += p;
                z_run = fmaf(pv, vz, z_run);
                mbar_wait(sb + BAR_FULLV + 8 * s, ph);
#pragma unroll
                for (int i = 0; i < 6; i++) {
                    const int4 v = lds128(st + kv_off + (i < 3 ? va_off : vb_off) + (i % 3) * 128);
                    acc[i][0] = fmaf(pv, (float)v.x, acc[i][0]);
                    acc[i][1] = fmaf(pv, (float)v.y, acc[i][1]);
                    acc[i][2] = fmaf(pv, (float)v.z, acc[i][2]);
                    acc[i][3] = fmaf(pv, (float)v.w, acc[i][3]);
                }
            }
            __syncwarp();
            if (lane == 0) mbar_arrive(sb + BAR_EMPTY + 8 * s);
            if (++s == STAGES) { s = 0; ph ^= 1; }
        } while (!(word & LAST_BIT));

        {
            const uint32_t tag = (word >> TAG_SHIFT) & 1;
            char* slot = reinterpret_cast<char*>(prm.scratch->part + (h * CPT + cin) * SLOT_WORDS);
            char* part_st = slot + (lane & 16) * 32 + j * 16 + (lane & 8);
            l_run += __shfl_xor_sync(0xffffffffu, l_run, 8);
            z_run += __shfl_xor_sync(0xffffffffu, z_run, 8);
            l_run += __shfl_xor_sync(0xffffffffu, l_run, 16);
            z_run += __shfl_xor_sync(0xffffffffu, z_run, 16);
            st_relaxed_b64(slot + r * 256 + QC * 4 + j * 8, __float_as_uint(m_run), tagged(l_run, tag));
            const bool od = (lane & 8) != 0;
#pragma unroll
            for (int i = 0; i < 3; i++) {
                float k[4];
#pragma unroll
                for (int c = 0; c < 4; c++) k[c] = acc[i][c] + __shfl_xor_sync(0xffffffffu, acc[i + 3][c], 16);
                const float z0 = (od ? k[2] : k[0]) + __shfl_xor_sync(0xffffffffu, od ? k[0] : k[2], 8);
                const float z1 = (od ? k[3] : k[1]) + __shfl_xor_sync(0xffffffffu, od ? k[1] : k[3], 8);
                st_relaxed_b64(part_st + i * 128 + (i == 2 ? 64 : i == 1 ? (j & 4) * 16 : 0),
                               __float_as_uint(z0 - z_run), tagged(z1 - z_run, tag));
            }
            if (lane < QUARTERS) mbox_post(prm.scratch->mbox + (h * QUARTERS + lane) * MBOX_STRIDE, 1u);
        }

        if (cw >= RSLOTS * 12 / 32) return;
        const int ft = threadIdx.x - W_CONS * 32;
        const int rs = ft / 12;
        constexpr int RPT = P_ROWS / RSLOTS;
        float a0 = 0.f, a1 = 0.f, a2 = 0.f, a3 = 0.f;
        mbar_wait(sb + BAR_W, 0);
        const uint32_t ra = sb + OFF_RV + rs * (RSTRIDE * 4 - QC * 4) + ft * 16;
        uint32_t va = sb + piece_off(0) + ft * 16, step = KV_BYTES;
#pragma unroll 1
        for (int p = 0; p < NP; p++) {
            float w[RPT];
#pragma unroll
            for (int i = 0; i < RPT; i += 4) {
                const int4 w4 = lds128(sb + OFF_W + p * (P_ROWS * 4) + (rs * RPT + i) * 4);
                w[i] = __int_as_float(w4.x); w[i + 1] = __int_as_float(w4.y);
                w[i + 2] = __int_as_float(w4.z); w[i + 3] = __int_as_float(w4.w);
            }
            mbar_wait(sb + BAR_FIN + 8 * p, 0);
#pragma unroll
            for (int i = 0; i < RPT; i++) {
                const int4 v = lds128(va + i * (RSLOTS * QC * 4));
                a0 = fmaf(w[i], (float)v.x, a0);
                a1 = fmaf(w[i], (float)v.y, a1);
                a2 = fmaf(w[i], (float)v.z, a2);
                a3 = fmaf(w[i], (float)v.w, a3);
            }
            va += step;
            step = STAGE_BYTES - step;
        }
        sts128f(ra, a0, a1, a2, a3);
        asm volatile("bar.arrive 3, %0;" ::"n"(RSLOTS * 12 + 32) : "memory");
        return;
    }

    if (warp >= W_GATHER) {
        asm volatile("bar.sync 0, %0;" ::"n"(THREADS) : "memory");
        const int sub = lane >= 13, quad = min(lane - sub * 13, 12);
        const int sg = 2 * (warp - W_GATHER) + sub;
        const float* src = prm.scratch->part + ((h0 + cin / QUARTERS) * CPT + sg) * SLOT_WORDS +
                           (cin % QUARTERS) * 64 + quad * 4;
        uint4 dt[NSL];
        mbar_wait(sb + BAR_INIT, 0);
        const uint32_t tag = lds32(sb + OFF_TAG);
        mbar_wait(sb + BAR_G, 0);
        int spin = 0;
        uint32_t bad;
#pragma unroll 1
        do {
            static_for<NSL>([&](auto bc) {
                constexpr int b = decltype(bc)::value;
                dt[b] = ld_relaxed_2xb64<b * SG * SLOT_WORDS * 4>(src);
            });
            bad = 0;
#pragma unroll
            for (int b = 0; b < NSL; b++) bad |= (dt[b].y ^ tag) | (dt[b].w ^ tag);
        } while (__any_sync(0xffffffffu, bad & 1u) && ++spin < (1 << 20));
        float mh[NSL], m = -INFINITY;
#pragma unroll
        for (int b = 0; b < NSL; b++) {
            mh[b] = __shfl_sync(0xffffffffu, __uint_as_float(dt[b].x), sub * 13 + 12);
            m = fmaxf(m, mh[b]);
        }
        float a0 = 0.f, a1 = 0.f, a2 = 0.f, a3 = 0.f;
#pragma unroll
        for (int b = 0; b < NSL; b++) {
            const float w = ex2(mh[b] - m);
            a0 = fmaf(w, __uint_as_float(dt[b].x), a0);
            a1 = fmaf(w, __uint_as_float(dt[b].y), a1);
            a2 = fmaf(w, __uint_as_float(dt[b].z), a2);
            a3 = fmaf(w, __uint_as_float(dt[b].w), a3);
        }
        if (lane < 26) sts128f(sb + OFF_RG + sg * (RSTRIDE * 4) + quad * 16, quad == 12 ? m : a0, a1, a2, a3);
        asm volatile("bar.arrive 2, %0;" ::"n"(GW * 32 + 32) : "memory");
        return;
    }

    if (warp == W_FIN) {
        if (elect_one()) {
            prefetch_map(&maps.ks);
            prefetch_map(&maps.kz);
            prefetch_map(&maps.vs);
            prefetch_map(&maps.vz);
            prefetch_map(&maps.v);
            prefetch_map(&maps.k);
        }
        asm volatile("bar.sync 0, %0;" ::"n"(THREADS) : "memory");
        const char* lptr = reinterpret_cast<const char*>(prm.scratch->logit + (h0 + cin / QUARTERS) * F_ROWS) + lane * 16;
        __nv_bfloat16* optr = prm.out + h0 * D + cin * QC + 2 * lane;
        mbar_wait(sb + BAR_INIT, 0);
        const uint32_t tag = lds32(sb + OFF_TAG);
        uint4 rec[NP];
        bool ok;
        int spin = 0;
        do {
            static_for<NP>([&](auto ic) { rec[decltype(ic)::value] = ld_relaxed_2xb64<decltype(ic)::value * 512>(lptr); });
            uint32_t bad = 0;
#pragma unroll
            for (int i = 0; i < NP; i++) bad |= (rec[i].y ^ tag) | (rec[i].w ^ tag);
            ok = (bad & 1u) == 0;
        } while (!__all_sync(0xffffffffu, ok) && ++spin < (1 << 20));
        float mF = -INFINITY, lF = 0.f, zF = 0.f;
#pragma unroll
        for (int i = 0; i < NP; i++) mF = fmaxf(mF, fmaxf(__uint_as_float(rec[i].y), __uint_as_float(rec[i].w)));
        mF = warp_max(mF);
        const uint32_t wa = sb + OFF_W + (2 * lane % RSLOTS) * (P_ROWS / RSLOTS * 4) + (2 * lane / RSLOTS) * 4;
#pragma unroll
        for (int i = 0; i < NP; i++) {
            const float p0 = ex2(__uint_as_float(rec[i].y) - mF), p1 = ex2(__uint_as_float(rec[i].w) - mF);
            const float a0 = p0 * bf_lo(rec[i].x), a1 = p1 * bf_lo(rec[i].z);
            lF += p0 + p1;
            zF = fmaf(a0, bf_hi(rec[i].x), fmaf(a1, bf_hi(rec[i].z), zF));
            sts32(wa + i * (P_ROWS * 4), __float_as_uint(a0));
            sts32(wa + i * (P_ROWS * 4) + P_ROWS / RSLOTS * 4, __float_as_uint(a1));
        }
        __syncwarp();
        if (lane == 0) mbar_arrive(sb + BAR_W);
#pragma unroll
        for (int o = 16; o > 0; o >>= 1) {
            lF += __shfl_xor_sync(0xffffffffu, lF, o);
            zF += __shfl_xor_sync(0xffffffffu, zF, o);
        }
        mbar_wait(sb + BAR_END, 0);
        if (lane == 0) {
            unsigned int* box = prm.scratch->mbox + (h0 * QUARTERS + cin) * MBOX_STRIDE;
            int seen = 0;
            do seen += mbox_take(box); while (seen < CPT && ++spin < (1 << 20));
            mbar_arrive(sb + BAR_G);
        }
        __syncwarp();
        const uint32_t col = sb + (uint32_t)min(lane, QC / 2 - 1) * 8;
        asm volatile("bar.sync 2, %0;" ::"r"(__float_as_uint(lF + zF) == 0xffffffffu ? 32 : GW * 32 + 32) : "memory");
        float2 ml[SG], ga[SG];
#pragma unroll
        for (int g = 0; g < SG; g++) {
            ml[g] = lds64f(sb + OFF_RG + g * (RSTRIDE * 4) + QC * 4);
            ga[g] = lds64f(col + OFF_RG + g * (RSTRIDE * 4));
        }
        float M = mF;
#pragma unroll
        for (int g = 0; g < SG; g++) M = fmaxf(M, ml[g].x);
        float wF = ex2(mF - M);
        float L = wF * lF, b0 = -wF * zF, b1 = b0;
#pragma unroll
        for (int g = 0; g < SG; g++) {
            const float w = ex2(ml[g].x - M);
            L = fmaf(w, ml[g].y, L);
            b0 = fmaf(w, ga[g].x, b0);
            b1 = fmaf(w, ga[g].y, b1);
        }
        const float inv = __fdividef(1.f, L);
        wF *= inv;
        b0 *= inv;
        b1 *= inv;
        asm volatile("bar.sync 3, %0;"
                     ::"r"(__any_sync(0xffffffffu, __float_as_uint(wF + b0 + b1) == 0xffffffffu) ? 32 : RSLOTS * 12 + 32) : "memory");
        float2 rv[RSLOTS];
#pragma unroll
        for (int g = 0; g < RSLOTS; g++) rv[g] = lds64f(col + OFF_RV + g * (RSTRIDE * 4));
        static_for<3>([&](auto lc) {
            constexpr int o = RSLOTS / 2 >> decltype(lc)::value;
#pragma unroll
            for (int g = 0; g < o; g++) {
                rv[g].x += rv[g + o].x;
                rv[g].y += rv[g + o].y;
            }
        });
        if (lane < QC / 2)
            *reinterpret_cast<__nv_bfloat162*>(optr) = __floats2bfloat162_rn(fmaf(wF, rv[0].x, b0), fmaf(wF, rv[0].y, b1));
        return;
    }

    __syncwarp();
    asm volatile("bar.arrive 0, %0;" ::"n"(THREADS) : "memory");
    if (!elect_one()) return;
    const uint64_t pol = evict_first_policy();
    unsigned long long* ctr = prm.scratch->ctr;
    constexpr int total = TICKETS - (STAGES - 1) * CPT;
    const unsigned long long inc = 1ull << (15 * team);
    unsigned long long ticket = draw(ctr, inc);
    const uint32_t t_begin = now();
    uint32_t w1 = 0, w2 = 0, w3 = 0;
    auto push = [&](uint32_t w) { w3 = w2; w2 = w1; w1 = w; };
    int s = 0, u = cin, k = 0, halves = 0, drawn = 0;
    uint32_t ph = 0;
    uint32_t t_draw = 0;
    bool init_done = false;
#pragma unroll 1
    for (;; k++) {
        const bool half = u >= UA;
        const int pos = half ? (u + UA) * (T / 2) : u * T;
        const int p8 = pos & ~7;
        const uint32_t fb = sb + BAR_FULLK + 8 * s;
        const uint32_t fv = sb + BAR_FULLV + 8 * s;
        const uint32_t dst = buf0 + s * STAGE_BYTES;
        halves += half;
        const bool gated = k >= STAGES && halves < STAGES;
        mbar_wait(sb + BAR_EMPTY + 8 * s, ph ^ 1);
        if (gated) mbar_wait(w3 & ~1u, w3 & 1u);
        if (k > 0) tma3d(dst + OFF_K, half ? &maps.kh : &maps.k, 0, pos, h0, fb, pol);
        bulk_load(dst + OFF_COS, prm.k_cos + (size_t)pos * D, half ? CS_BYTES / 2 : CS_BYTES, fb);
        bulk_load(dst + OFF_SIN, prm.k_sin + (size_t)pos * D, half ? CS_BYTES / 2 : CS_BYTES, fb);
        tma2d(dst + OFF_KS, &maps.ks, p8, h0, fb);
        tma2d(dst + OFF_KZ, &maps.kz, p8, h0, fb);
        tma2d(dst + OFF_VS, &maps.vs, p8, h0, fb);
        tma2d(dst + OFF_VZ, &maps.vz, p8, h0, fb);
        if (k >= STAGES) ticket = draw(ctr, inc);
        if ((u & (TEAMS - 1)) == team && !half) {
            l2_prefetch(prm.k_cos + (size_t)(pos + CS_AHEAD * T) * D, CS_BYTES);
            l2_prefetch(prm.k_sin + (size_t)(pos + CS_AHEAD * T) * D, CS_BYTES);
        }
        if (half) t_draw = now();
        push(fb | ph);
        if ((unsigned)(pos - F0) < (unsigned)F_ROWS) {
            mbar_arrive(fv);
            prefetch_map(&maps.kh);
            prefetch_map(&maps.vh);
            prefetch_map(&maps.vf);
        } else {
            if (gated) mbar_wait(w3 & ~1u, w3 & 1u);
            mbar_expect_tx(fv, half ? KV_BYTES / 2 : KV_BYTES);
            tma3d(dst + OFF_V, half ? &maps.vh : &maps.v, 0, pos, h0, fv, pol);
            push(fv | ph);
        }
        int un = u + CPT;
        uint32_t tag = 0;
        if (k >= STAGES - 1) {
            uint32_t lo, hi;
            asm volatile("st.shared.b64 [%2], %3;\nld.volatile.shared.v2.u32 {%0,%1}, [%2];"
                         : "=r"(lo), "=r"(hi) : "r"(sb + OFF_TICKET), "l"(ticket) : "memory");
            const int t01 = (int)(lo & 0x3fffffff), t23 = (int)(__funnelshift_r(lo, hi, 30) & 0x3fffffff);
            const int t = ((team & 2 ? t23 : t01) >> (15 * (team & 1))) & 0x7fff;
            drawn = (t01 & 0x7fff) + (t01 >> 15) + (t23 & 0x7fff) + (t23 >> 15);
            tag = ~hi >> 31;
            un = STAGES * CPT + t;
        }
        const bool start_fin = !init_done && un >= TICKETS - 2 * CPT;
        init_done |= start_fin;
        sts32(sb + OFF_UIDX + 4 * s, pos | (tag << TAG_SHIFT) | (un >= TICKETS ? LAST_BIT : 0));
        mbar_expect_tx(fb, half ? KSIDE_BYTES - KV_BYTES / 2 - CS_BYTES : KSIDE_BYTES);
        if (start_fin) {
            sts32(sb + OFF_TAG, tag);
            mbar_arrive(sb + BAR_INIT);
        }
        if (un >= TICKETS) break;
        u = un;
        if (++s == STAGES) { s = 0; ph ^= 1; }
    }
    mbar_arrive(sb + BAR_END);
    if (drawn == TEAMS * total - 1) draw(ctr, (1ull << 63) - total * 0x0000200040008001ull);
    uint32_t t_next = now();
    int dt = (int)(t_draw - t_next) +
             (int)(((t_draw - t_begin) >> 4) * (uint32_t)(PACE_BASE + min(TEAMS * total - drawn, 512)) / (PACE_DIV / 16));
    dt = max(dt, 0) / NP;
    if (halves < STAGES) {
        mbar_wait(sb + BAR_EMPTY + 8 * s, ph);
        dt = 0;
    }
#pragma unroll 1
    for (int p = 0; p < NP; p++) {
        const uint32_t fb = sb + BAR_FIN + 8 * p;
        t_next += dt;
        while ((int)(now() - t_next) < 0 && !mbar_test(w2 & ~1u, w2 & 1u)) {}
        mbar_expect_tx(fb, PIECE_BYTES);
        tma3d(sb + piece_off(p), &maps.vf, (cin % QUARTERS) * QC, F0 + p * P_ROWS, h0 + cin / QUARTERS, fb, pol);
        push(fb);
    }
}

__global__ void __launch_bounds__(128)
fallback_partial_kernel(const Params prm, const int* qv, const __nv_bfloat16* ks, const __nv_bfloat16* kz,
                        const __nv_bfloat16* vs, const __nv_bfloat16* vz) {
    const int h = blockIdx.y, slot = blockIdx.x * 4 + (threadIdx.x >> 5), lane = threadIdx.x & 31;
    float qa[3], qb[3], acc[6] = {0.f, 0.f, 0.f, 0.f, 0.f, 0.f};
    for (int i = 0; i < 3; i++) {
        const int d = 32 * i + lane;
        const __nv_bfloat16 x1 = prm.q[h * D + d], x2 = prm.q[h * D + d + HALF];
        qa[i] = __bfloat162float(__hsub_rn(__hmul_rn(x1, prm.q_cos[d]), __hmul_rn(x2, prm.q_sin[d])));
        qb[i] = __bfloat162float(__hadd_rn(__hmul_rn(x2, prm.q_cos[d + HALF]), __hmul_rn(x1, prm.q_sin[d + HALF])));
    }
    float m = -3e38f, l = 0.f;
    for (int pos = slot; pos < S; pos += CPT) {
        const size_t row = (size_t)h * S + pos;
        const float z = __bfloat162float(kz[row]);
        float dot = 0.f;
        for (int i = 0; i < 3; i++) {
            const int d = 32 * i + lane;
            const float a = (float)prm.qk[row * D + d] - z, b = (float)prm.qk[row * D + d + HALF] - z;
            const __nv_bfloat16* c = prm.k_cos + pos * D + d;
            const __nv_bfloat16* sn = prm.k_sin + pos * D + d;
            dot += qa[i] * (a * __bfloat162float(c[0]) - b * __bfloat162float(sn[0])) +
                   qb[i] * (b * __bfloat162float(c[HALF]) + a * __bfloat162float(sn[HALF]));
        }
        for (int o = 16; o > 0; o >>= 1) dot += __shfl_xor_sync(0xffffffffu, dot, o);
        const float sv = dot * __bfloat162float(ks[row]) * QK_SCALE;
        const float m_new = fmaxf(m, sv), alpha = ex2(m - m_new), p = ex2(sv - m_new);
        const float pv = p * __bfloat162float(vs[row]), zv = __bfloat162float(vz[row]);
        m = m_new;
        l = l * alpha + p;
        for (int i = 0; i < 6; i++) acc[i] = acc[i] * alpha + pv * ((float)qv[row * D + 32 * i + lane] - zv);
    }
    float* dst = prm.scratch->part + (h * CPT + slot) * SLOT_WORDS;
    for (int i = 0; i < 6; i++) dst[32 * i + lane] = acc[i];
    if (lane == 0) {
        dst[D] = m;
        dst[D + 1] = l;
    }
}

__global__ void __launch_bounds__(D) fallback_merge_kernel(const Params prm) {
    const float* src = prm.scratch->part + blockIdx.x * CPT * SLOT_WORDS;
    float m = -3e38f, l = 0.f, o = 0.f;
    for (int c = 0; c < CPT; c++) m = fmaxf(m, src[c * SLOT_WORDS + D]);
    for (int c = 0; c < CPT; c++) {
        const float w = ex2(src[c * SLOT_WORDS + D] - m);
        l += w * src[c * SLOT_WORDS + D + 1];
        o += w * src[c * SLOT_WORDS + threadIdx.x];
    }
    prm.out[blockIdx.x * D + threadIdx.x] = __float2bfloat16_rn(o / l);
}

typedef CUresult (*EncodeTiledFn)(CUtensorMap*, CUtensorMapDataType, cuuint32_t, void*, const cuuint64_t*,
                                  const cuuint64_t*, const cuuint32_t*, const cuuint32_t*,
                                  CUtensorMapInterleave, CUtensorMapSwizzle, CUtensorMapL2promotion,
                                  CUtensorMapFloatOOBfill);

void make_kv_map(EncodeTiledFn enc, CUtensorMap* m, const void* ptr, int cols, int rows, int heads,
                 CUtensorMapL2promotion promo) {
    cuuint64_t dims[3] = {(cuuint64_t)D, (cuuint64_t)S, (cuuint64_t)H};
    cuuint64_t strides[2] = {(cuuint64_t)D * 4, (cuuint64_t)S * D * 4};
    cuuint32_t box[3] = {(cuuint32_t)cols, (cuuint32_t)rows, (cuuint32_t)heads};
    cuuint32_t es[3] = {1, 1, 1};
    enc(m, CU_TENSOR_MAP_DATA_TYPE_INT32, 3, const_cast<void*>(ptr), dims, strides, box, es,
        CU_TENSOR_MAP_INTERLEAVE_NONE, CU_TENSOR_MAP_SWIZZLE_NONE, promo, CU_TENSOR_MAP_FLOAT_OOB_FILL_NONE);
}

void make_scale_map(EncodeTiledFn enc, CUtensorMap* m, const void* ptr) {
    cuuint64_t dims[2] = {(cuuint64_t)S, (cuuint64_t)H};
    cuuint64_t strides[1] = {(cuuint64_t)S * 2};
    cuuint32_t box[2] = {8, (cuuint32_t)G};
    cuuint32_t es[2] = {1, 1};
    enc(m, CU_TENSOR_MAP_DATA_TYPE_BFLOAT16, 2, const_cast<void*>(ptr), dims, strides, box, es,
        CU_TENSOR_MAP_INTERLEAVE_NONE, CU_TENSOR_MAP_SWIZZLE_NONE, CU_TENSOR_MAP_L2_PROMOTION_L2_256B,
        CU_TENSOR_MAP_FLOAT_OOB_FILL_NONE);
}

}

extern "C" void kernel_launch(void* const* d_in, const int* in_sizes, int n_in, void* d_out, int out_size) {
    (void)in_sizes; (void)n_in; (void)out_size;
    static EncodeTiledFn enc = nullptr;
    static Scratch* scratch = nullptr;
    static int sms = 0;
    if (!enc) {
        void* fn = nullptr;
        cudaDriverEntryPointQueryResult qr;
        cudaGetDriverEntryPoint("cuTensorMapEncodeTiled", &fn, cudaEnableDefault, &qr);
        enc = (EncodeTiledFn)fn;
        int dev = 0;
        cudaGetDevice(&dev);
        cudaDeviceGetAttribute(&sms, cudaDevAttrMultiProcessorCount, dev);
        cudaGetSymbolAddress((void**)&scratch, g_scratch);
        cudaFuncSetAttribute(kv_decode_kernel, cudaFuncAttributeMaxDynamicSharedMemorySize, SMEM_BYTES);
    }
    Params prm;
    prm.q = (const __nv_bfloat16*)d_in[0];
    prm.qk = (const int*)d_in[1];
    prm.q_cos = (const __nv_bfloat16*)d_in[7];
    prm.q_sin = (const __nv_bfloat16*)d_in[8];
    prm.k_cos = (const __nv_bfloat16*)d_in[9];
    prm.k_sin = (const __nv_bfloat16*)d_in[10];
    prm.out = (__nv_bfloat16*)d_out;
    prm.scratch = scratch;
    if (sms < TEAMS * CPT) {
        fallback_partial_kernel<<<dim3(CPT / 4, H), 128>>>(
            prm, (const int*)d_in[4], (const __nv_bfloat16*)d_in[2], (const __nv_bfloat16*)d_in[3],
            (const __nv_bfloat16*)d_in[5], (const __nv_bfloat16*)d_in[6]);
        fallback_merge_kernel<<<H, D>>>(prm);
        return;
    }
    Maps maps;
    make_kv_map(enc, &maps.k, prm.qk, D, T, G, CU_TENSOR_MAP_L2_PROMOTION_L2_128B);
    make_kv_map(enc, &maps.v, d_in[4], D, T, G, CU_TENSOR_MAP_L2_PROMOTION_L2_128B);
    make_kv_map(enc, &maps.kh, prm.qk, D, T / 2, G, CU_TENSOR_MAP_L2_PROMOTION_L2_128B);
    make_kv_map(enc, &maps.vh, d_in[4], D, T / 2, G, CU_TENSOR_MAP_L2_PROMOTION_L2_128B);
    make_kv_map(enc, &maps.vf, d_in[4], QC, P_ROWS, 1, CU_TENSOR_MAP_L2_PROMOTION_NONE);
    make_scale_map(enc, &maps.ks, d_in[2]);
    make_scale_map(enc, &maps.kz, d_in[3]);
    make_scale_map(enc, &maps.vs, d_in[5]);
    make_scale_map(enc, &maps.vz, d_in[6]);

    kv_decode_kernel<<<TEAMS * CPT, THREADS, SMEM_BYTES>>>(prm, maps);
}
```
